```python
import torch

def _softmax(x, axis=-1):
    return torch.softmax(x, dim=axis)

def _gelu(x):
    return torch.nn.functional.gelu(x, approximate='tanh')

def _silu(x):
    return torch.nn.functional.silu(x)

def _sigmoid(x):
    return torch.sigmoid(x)

def _layernorm(x, axis=-1, eps=1e-05):
    m = x.mean(dim=axis, keepdim=True)
    v = x.var(dim=axis, keepdim=True, unbiased=False)
    return (x - m) / torch.sqrt(v + eps)

def _scatter_add(tgt, idx, src, axis=0):
    return tgt.clone().index_add_(axis, idx, src)

def _segment_sum(src, seg, n):
    out = torch.zeros((n,) + src.shape[1:], dtype=src.dtype)
    return out.index_add_(0, seg, src)

def _pad(x, pw):
    flat = tuple((v for pair in reversed(pw) for v in pair))
    return torch.nn.functional.pad(x, flat)
kernel_name = 'adaLN_cond__sliding_block_cached__dense_activation_silu__decode'

def setup_inputs():

    _w = lambda a: (lambda t: t.to(torch.bfloat16) if t.is_floating_point() else t)(torch.as_tensor(a))

    def _A_setup():
        B, Sq, D = (1, 1, 576)
        Hq, Hkv, Sk, Dh = (32, 16, 65536, 128)
        assert Hq % Hkv == 0, (Hq, Hkv)
        return {'x': _w((lambda *s: torch.randn(*s, dtype=torch.bfloat16) * 0.05)(B, Sq, D)), 'k_cache': _w((lambda *s: torch.randn(*s, dtype=torch.bfloat16) * 3.2)(B, Hkv, Sk, Dh)), 'v_cache': _w((lambda *s: torch.randn(*s, dtype=torch.bfloat16) * 1.6)(B, Hkv, Sk, Dh)), 'wq': _w((lambda *s: torch.randn(*s, dtype=torch.bfloat16) * 3.2)(D, Hq * Dh) * D ** (-0.5)), 'wo': _w((lambda *s: torch.randn(*s, dtype=torch.bfloat16) * 1.6)(Hq * Dh, D) * (Hq * Dh) ** (-0.5))}
    _A_in = _A_setup()

    def _B_setup():
        B, S, D, F = (1, 1, 576, 4608)
        return {'x': _w((lambda *s: torch.randn(*s, dtype=torch.bfloat16) * 0.05)(B, S, D)), 'w1': _w((lambda *s: torch.randn(*s, dtype=torch.bfloat16) * 3.2)(D, F) * D ** (-0.5)), 'w2': _w((lambda *s: torch.randn(*s, dtype=torch.bfloat16) * 3.2)(F, D) * F ** (-0.5))}
    _B_in = _B_setup()
    return {'A_x': _A_in['x'], 'A_k_cache': _A_in['k_cache'], 'A_v_cache': _A_in['v_cache'], 'A_wq': _A_in['wq'], 'A_wo': _A_in['wo'], 'B_x': _B_in['x'], 'B_w1': _B_in['w1'], 'B_w2': _B_in['w2'], 'c': _w((lambda *s: torch.randn(*s, dtype=torch.bfloat16) * 0.2)(1, 576) * 8.0), 'w_mod': _w((lambda *s: torch.randn(*s, dtype=torch.bfloat16) * 0.2)(576, 6 * 576) * 576 ** (-0.5) * 8.0)}

def reference(A_x, A_k_cache, A_v_cache, A_wq, A_wo, B_x, B_w1, B_w2, c, w_mod):

    def _A_ref(x, k_cache, v_cache, wq, wo):
        B, Sq, D = x.shape
        Hq, Dh = (32, 128)
        Hkv, Sk = (k_cache.shape[1], k_cache.shape[2])
        W = min(4096, max(256, Sk // 4))
        rep = Hq // Hkv
        q = (lambda x, *d: x.permute(*d))((x @ wq).reshape(B, Sq, Hq, Dh), 0, 2, 1, 3)
        k = (lambda x, n, axis: torch.repeat_interleave(x, n, dim=axis))(k_cache[:, :, Sk - W:, :], rep, axis=1)
        v = (lambda x, n, axis: torch.repeat_interleave(x, n, dim=axis))(v_cache[:, :, Sk - W:, :], rep, axis=1)
        scores = torch.einsum('bhqd,bhkd->bhqk', q, k) * Dh ** (-0.5)
        p = _softmax(scores, axis=-1)
        o = torch.einsum('bhqk,bhkd->bhqd', p, v)
        return (lambda x, *d: x.permute(*d))(o, 0, 2, 1, 3).reshape(B, Sq, Hq * Dh) @ wo

    def _B_ref(x, w1, w2):
        h = torch.einsum('bsd,df->bsf', x, w1)
        h = _silu(h)
        out = torch.einsum('bsf,fd->bsd', h, w2)
        return out
    x = A_x
    mod = (_silu(c) @ w_mod).reshape(c.shape[0], 6, 1, -1)
    sa, ca, ga, sb, cb, gb = (mod[:, 0].clone(), mod[:, 1].clone(), mod[:, 2].clone(), mod[:, 3].clone(), mod[:, 4].clone(), mod[:, 5].clone())
    h = _layernorm(x, axis=-1) * (1 + ca) + sa
    x = x + ga * _A_ref(h, A_k_cache, A_v_cache, A_wq, A_wo)
    h = _layernorm(x, axis=-1) * (1 + cb) + sb
    x = x + gb * _B_ref(h, B_w1, B_w2)
    return x
```

```cpp
#include <cuda.h>
#include <cuda_bf16.h>
#include <cuda_runtime.h>
#include <stdint.h>

namespace {

constexpr int D = 576, FF = 4608, NKV = 16, SK = 65536, WINDOW = 4096, DH = 128;
constexpr int CS = 6;
constexpr int NCW = 12;
constexpr int NCT = NCW * 32;
constexpr int MONW = 0;
constexpr int NTHREADS = NCT + 32 + MONW;
constexpr int MAXT = 11;

#define DEPTH_A 3
#define DEPTH_KV 3
#define DEPTH_WO 3
#define DEPTH_W1 2
#define DEPTH_W2 2
#define PACE_GBPS 0
#define PACE_LEAD 0
#define TLB_WARM 0
#define NFIRST 2
#define WQ_DELAY 0
#define KPREFETCH 0

constexpr int P_MOD = 208, P_WO = 208, P_W1 = 112, P_W2 = 1200;
constexpr int SZ_MOD = 72 * P_MOD, SZ_WQ = 32 * 512, SZ_KV = 64 * 256, SZ_WO = 64 * P_WO, SZ_W1 = 144 * P_W1,
              SZ_W2 = 16 * P_W2;
constexpr int O_WQ = 0, O_MODA = O_WQ + 3 * SZ_WQ, O_MODB = O_MODA + SZ_MOD;
constexpr int O_WO = 0, O_W1A = O_WO + 4 * SZ_WO;
constexpr int O_RING = 95 * 1024, NRING = 6, NSLOT = 8;
constexpr int O_XSLOT = O_RING - 2 * SZ_KV;
constexpr int O_W1B = O_RING, O_W2 = O_W1B + 2 * SZ_W1;
constexpr int O_MISC = O_RING + NRING * SZ_KV;
static_assert(O_MODB + 2 * SZ_MOD <= O_RING && O_W1A + 2 * SZ_W1 <= O_RING, "area A");
static_assert(O_W2 + 3 * SZ_W2 <= O_MISC, "ring");
static_assert(O_XSLOT >= O_MODA && O_XSLOT % 1024 == 0 && O_XSLOT >= O_WO + 4 * SZ_WO, "extra slots");
__device__ __forceinline__ uint32_t slot_off(int slot) { return slot < NRING ? O_RING + slot * SZ_KV : O_XSLOT + (slot - NRING) * SZ_KV; }
constexpr int O_QBUF = O_MISC;
constexpr int O_OBUF = O_QBUF + 6144;
constexpr int O_MLBUF = O_OBUF + 6144;
constexpr int O_X2 = O_MLBUF + 128;
constexpr int O_G1P = O_X2 + 2304;
constexpr int O_SB = O_G1P + 2304;
constexpr int O_D0 = O_SB + 2304;
constexpr int O_XS = O_D0 + 2304;
constexpr int O_SC = O_XS + 2304;
constexpr int O_HV = O_SC + 1152;
constexpr int O_QV = O_HV + 256;
constexpr int PV_PITCH = 712;
constexpr int O_PV = O_QV + 512;
constexpr int O_OV = O_PV + 2944;
constexpr int O_H2 = O_OV + 512;
constexpr int O_RED1 = O_H2 + 1152;
constexpr int O_GA = O_RED1 + 768;
constexpr int O_GB = O_GA + 384;
constexpr int O_WMAX = O_GB + 384;
constexpr int O_WL = O_WMAX + 128;
constexpr int O_TAG = O_WL + 112;
constexpr int O_BAR = O_WL + 128;
constexpr int B_MODA = 0, B_WQ = 1, B_MODB = 4, B_K = 6, B_V = B_K + MAXT, B_WO = B_V + MAXT, B_W1 = B_WO + 4,
              B_W2 = B_W1 + 4, B_EMPTY = B_W2 + 3  , B_AFREE = B_EMPTY + 2 * MAXT, B_MODFREE = B_AFREE + 1, B_XQ = B_MODFREE + 1,
              B_XB = B_XQ + 1, B_XC = B_XB + 1, B_XG = B_XC + 1, B_XD = B_XG + 1, B_GATES = B_XD + 1,
              NBAR = B_GATES + 1;
constexpr int SMEM_BYTES = O_BAR + NBAR * 8;
static_assert(SMEM_BYTES <= 232448, "smem");

struct alignas(128) Scratch {
    uint4 a1[2 * 6 * 6 * 8 * 8];
    uint4 a2[4 * 6 * 6 * 4 * 8];
    uint4 c1[6 * 6 * 16 * 8];
    uint4 d1[6 * 6 * 16 * 8];
    unsigned epoch;
};
__device__ Scratch g_scr;

#define PROF(i) do {} while (0)
#define PROF1(i) do {} while (0)

__device__ __forceinline__ void mbar_init(uint32_t bar, uint32_t cnt) {
    asm volatile("mbarrier.init.shared::cta.b64 [%0], %1;" ::"r"(bar), "r"(cnt) : "memory");
}
__device__ __forceinline__ void mbar_expect_tx(uint32_t bar, uint32_t bytes) {
    asm volatile("mbarrier.arrive.expect_tx.shared::cta.b64 _, [%0], %1;" ::"r"(bar), "r"(bytes) : "memory");
}
__device__ __forceinline__ void mbar_arrive(uint32_t bar) {
    asm volatile("mbarrier.arrive.shared::cta.b64 _, [%0];" ::"r"(bar) : "memory");
}
__device__ __forceinline__ void mbar_wait(uint32_t bar) {
    uint32_t ok;
    int n = 0;
    do {
        asm volatile("{\n.reg .pred p;\nmbarrier.try_wait.parity.shared::cta.b64 p, [%1], 0;\nselp.u32 %0, 1, 0, p;\n}"
                     : "=r"(ok) : "r"(bar) : "memory");
        if (++n > (1 << 22)) __trap();
    } while (!ok);
}
__device__ __forceinline__ void mbar_wait_cluster(uint32_t bar) {
    uint32_t ok;
    int n = 0;
    do {
        asm volatile("{\n.reg .pred p;\nmbarrier.try_wait.parity.acquire.cluster.shared::cta.b64 p, [%1], 0;\nselp.u32 %0, 1, 0, p;\n}"
                     : "=r"(ok) : "r"(bar) : "memory");
        if (++n > (1 << 22)) __trap();
    } while (!ok);
}
__device__ __forceinline__ uint32_t gtime32() { uint32_t t; asm volatile("mov.u32 %0, %%globaltimer_lo;" : "=r"(t)); return t; }
__device__ __forceinline__ void bar_sync(int id, int n) { asm volatile("bar.sync %0, %1;" ::"r"(id), "r"(n) : "memory"); }
__device__ __forceinline__ void bar_arrive(int id, int n) { asm volatile("bar.arrive %0, %1;" ::"r"(id), "r"(n) : "memory"); }
__device__ __forceinline__ void tma2d(uint32_t dst, const CUtensorMap* m, int c0, int c1, uint32_t bar, uint64_t pol) {
    asm volatile("cp.async.bulk.tensor.2d.shared::cluster.global.mbarrier::complete_tx::bytes.L2::cache_hint [%0], [%1, {%3, %4}], [%2], %5;"
                 ::"r"(dst), "l"(m), "r"(bar), "r"(c0), "r"(c1), "l"(pol) : "memory");
}
__device__ __forceinline__ void tma3d(uint32_t dst, const CUtensorMap* m, int c0, int c1, int c2, uint32_t bar, uint64_t pol) {
    asm volatile("cp.async.bulk.tensor.3d.shared::cluster.global.mbarrier::complete_tx::bytes.L2::cache_hint [%0], [%1, {%3, %4, %5}], [%2], %6;"
                 ::"r"(dst), "l"(m), "r"(bar), "r"(c0), "r"(c1), "r"(c2), "l"(pol) : "memory");
}
__device__ __forceinline__ uint32_t mapa(uint32_t addr, uint32_t rank) {
    uint32_t r;
    asm("mapa.shared::cluster.u32 %0, %1, %2;" : "=r"(r) : "r"(addr), "r"(rank));
    return r;
}
__device__ __forceinline__ void st_async4(uint32_t addr, float a, float b, float c, float d, uint32_t bar) {
    asm volatile("st.async.weak.shared::cluster.mbarrier::complete_tx::bytes.v4.f32 [%0], {%1,%2,%3,%4}, [%5];"
                 ::"r"(addr), "f"(a), "f"(b), "f"(c), "f"(d), "r"(bar) : "memory");
}
__device__ __forceinline__ void st_async2(uint32_t addr, float a, float b, uint32_t bar) {
    asm volatile("st.async.weak.shared::cluster.mbarrier::complete_tx::bytes.v2.f32 [%0], {%1,%2}, [%3];"
                 ::"r"(addr), "f"(a), "f"(b), "r"(bar) : "memory");
}
__device__ __forceinline__ void st_msg(uint4* p, float a, float b, uint32_t tag) {
    asm volatile("{\n.reg .b128 t;\n.reg .b64 lo, hi;\nmov.b64 lo, {%1,%2};\nmov.b64 hi, {%3,%3};\nmov.b128 t, {lo,hi};\n"
                 "st.relaxed.gpu.global.b128 [%0], t;\n}"
                 ::"l"(p), "r"(__float_as_uint(a)), "r"(__float_as_uint(b)), "r"(tag) : "memory");
}
__device__ __forceinline__ uint4 ld_msg(const uint4* p) {
    uint4 v;
    asm volatile("{\n.reg .b128 t;\n.reg .b64 lo, hi;\nld.relaxed.gpu.global.b128 t, [%4];\nmov.b128 {lo,hi}, t;\n"
                 "mov.b64 {%0,%1}, lo;\nmov.b64 {%2,%3}, hi;\n}"
                 : "=r"(v.x), "=r"(v.y), "=r"(v.z), "=r"(v.w) : "l"(p) : "memory");
    return v;
}
template <int N>
__device__ __forceinline__ float2 gather_msgs(const uint4* p, int stride, uint32_t tag) {
    uint4 v[N];
    int n = 0;
    bool ok;
    do {
        ok = true;
#pragma unroll
        for (int i = 0; i < N; i++) v[i] = ld_msg(p + i * stride);
#pragma unroll
        for (int i = 0; i < N; i++) ok = ok && (v[i].w == tag);
        if (++n > (1 << 21)) __trap();
    } while (!__all_sync(0xffffffffu, ok));
    float a = __uint_as_float(v[0].x), b = __uint_as_float(v[0].y);
#pragma unroll
    for (int i = 1; i < N; i++) { a += __uint_as_float(v[i].x); b += __uint_as_float(v[i].y); }
    a += __shfl_xor_sync(0xffffffffu, a, 8);
    b += __shfl_xor_sync(0xffffffffu, b, 8);
    a += __shfl_xor_sync(0xffffffffu, a, 16);
    b += __shfl_xor_sync(0xffffffffu, b, 16);
    return make_float2(a, b);
}
__device__ __forceinline__ void gather_msgs2(const uint4* p, const uint4* q, uint32_t tag, float2& u, float2& w, uint32_t sm) {
    uint4 v[4];
    int n = 0;
    bool ok;
    do {
        v[0] = ld_msg(p); v[1] = ld_msg(p + 32); v[2] = ld_msg(q); v[3] = ld_msg(q + 32);
        ok = v[0].w == tag && v[1].w == tag && v[2].w == tag && v[3].w == tag;
        if (++n > (1 << 21)) __trap();
    } while (!__all_sync(0xffffffffu, ok));
    float a = __uint_as_float(v[0].x) + __uint_as_float(v[1].x), b = __uint_as_float(v[0].y) + __uint_as_float(v[1].y);
    float c = __uint_as_float(v[2].x) + __uint_as_float(v[3].x), d = __uint_as_float(v[2].y) + __uint_as_float(v[3].y);
#pragma unroll
    for (int o = 8; o <= 16; o <<= 1) {
        a += __shfl_xor_sync(0xffffffffu, a, o); b += __shfl_xor_sync(0xffffffffu, b, o);
        c += __shfl_xor_sync(0xffffffffu, c, o); d += __shfl_xor_sync(0xffffffffu, d, o);
    }
    u = make_float2(a, b);
    w = make_float2(c, d);
}
__device__ __forceinline__ void ldsm4(uint32_t (&a)[4], uint32_t addr) {
    asm volatile("ldmatrix.sync.aligned.m8n8.x4.shared.b16 {%0,%1,%2,%3}, [%4];"
                 : "=r"(a[0]), "=r"(a[1]), "=r"(a[2]), "=r"(a[3]) : "r"(addr) : "memory");
}
__device__ __forceinline__ void ldsm4t(uint32_t (&a)[4], uint32_t addr) {
    asm volatile("ldmatrix.sync.aligned.m8n8.x4.trans.shared.b16 {%0,%1,%2,%3}, [%4];"
                 : "=r"(a[0]), "=r"(a[1]), "=r"(a[2]), "=r"(a[3]) : "r"(addr) : "memory");
}
__device__ __forceinline__ void ldsm2t(uint32_t (&a)[2], uint32_t addr) {
    asm volatile("ldmatrix.sync.aligned.m8n8.x2.trans.shared.b16 {%0,%1}, [%2];"
                 : "=r"(a[0]), "=r"(a[1]) : "r"(addr) : "memory");
}
__device__ __forceinline__ void mma16(float (&c)[4], const uint32_t (&a)[4], uint32_t b0, uint32_t b1) {
    asm volatile("mma.sync.aligned.m16n8k16.row.col.f32.bf16.bf16.f32 {%0,%1,%2,%3}, {%4,%5,%6,%7}, {%8,%9}, {%0,%1,%2,%3};"
                 : "+f"(c[0]), "+f"(c[1]), "+f"(c[2]), "+f"(c[3])
                 : "r"(a[0]), "r"(a[1]), "r"(a[2]), "r"(a[3]), "r"(b0), "r"(b1));
}
__device__ __forceinline__ void mma8(float (&c)[4], const uint32_t (&a)[2], uint32_t b0) {
    asm volatile("mma.sync.aligned.m16n8k8.row.col.f32.bf16.bf16.f32 {%0,%1,%2,%3}, {%4,%5}, {%6}, {%0,%1,%2,%3};"
                 : "+f"(c[0]), "+f"(c[1]), "+f"(c[2]), "+f"(c[3]) : "r"(a[0]), "r"(a[1]), "r"(b0));
}
__device__ __forceinline__ uint32_t lds32(uint32_t a) { uint32_t v; asm volatile("ld.shared.b32 %0, [%1];" : "=r"(v) : "r"(a) : "memory"); return v; }
__device__ __forceinline__ float ldsf(uint32_t a) { float v; asm volatile("ld.shared.f32 %0, [%1];" : "=f"(v) : "r"(a) : "memory"); return v; }
__device__ __forceinline__ float2 ldsf2(uint32_t a) { float2 v; asm volatile("ld.shared.v2.f32 {%0,%1}, [%2];" : "=f"(v.x), "=f"(v.y) : "r"(a) : "memory"); return v; }
__device__ __forceinline__ float4 ldsf4(uint32_t a) { float4 v; asm volatile("ld.shared.v4.f32 {%0,%1,%2,%3}, [%4];" : "=f"(v.x), "=f"(v.y), "=f"(v.z), "=f"(v.w) : "r"(a) : "memory"); return v; }
__device__ __forceinline__ uint4 lds128(uint32_t a) { uint4 v; asm volatile("ld.shared.v4.b32 {%0,%1,%2,%3}, [%4];" : "=r"(v.x), "=r"(v.y), "=r"(v.z), "=r"(v.w) : "r"(a) : "memory"); return v; }
__device__ __forceinline__ void sts128(uint32_t a, uint32_t x, uint32_t y, uint32_t z, uint32_t w) { asm volatile("st.shared.v4.b32 [%0], {%1,%2,%3,%4};" ::"r"(a), "r"(x), "r"(y), "r"(z), "r"(w) : "memory"); }
__device__ __forceinline__ void stsf(uint32_t a, float v) { asm volatile("st.shared.f32 [%0], %1;" ::"r"(a), "f"(v) : "memory"); }
__device__ __forceinline__ void stsf2(uint32_t a, float x, float y) { asm volatile("st.shared.v2.f32 [%0], {%1,%2};" ::"r"(a), "f"(x), "f"(y) : "memory"); }
__device__ __forceinline__ void sts32(uint32_t a, uint32_t v) { asm volatile("st.shared.b32 [%0], %1;" ::"r"(a), "r"(v) : "memory"); }
__device__ __forceinline__ void sts_bf16(uint32_t a, float v) {
    asm volatile("st.shared.b16 [%0], %1;" ::"r"(a), "h"(__bfloat16_as_ushort(__float2bfloat16_rn(v))) : "memory");
}
__device__ __forceinline__ float bf16r(float x) { return __bfloat162float(__float2bfloat16_rn(x)); }
__device__ __forceinline__ float silu_bf16(float x) { return bf16r(__fdividef(x, 1.0f + __expf(-x))); }

template <int PITCH>
__device__ __forceinline__ uint32_t gemv_addr(uint32_t tile, int col0, int lane) {
    return tile + ((lane & 7) + 8 * (lane >> 4)) * PITCH + (col0 + 8 * ((lane >> 3) & 1)) * 2;
}
template <int PITCH, int NK>
__device__ __forceinline__ void gemv_tile(float (&acc0)[4], float (&acc1)[4], uint32_t a_addr, uint32_t v_addr) {
#pragma unroll
    for (int ks = 0; ks < NK; ks++) {
        uint32_t a[4];
        ldsm4t(a, a_addr + ks * 16 * PITCH);
        const uint32_t b0 = lds32(v_addr + ks * 32), b1 = lds32(v_addr + ks * 32 + 16);
        if (ks & 1) mma16(acc1, a, b0, b1); else mma16(acc0, a, b0, b1);
    }
}

__device__ __forceinline__ float2 ln_stats(const float (&x)[18], float shift) {
    float s1 = 0.f, s2 = 0.f;
#pragma unroll
    for (int i = 0; i < 18; i++) { const float d = x[i] - shift; s1 += d; s2 = fmaf(d, d, s2); }
#pragma unroll
    for (int o = 16; o; o >>= 1) { s1 += __shfl_xor_sync(0xffffffffu, s1, o); s2 += __shfl_xor_sync(0xffffffffu, s2, o); }
    const float md = s1 * (1.0f / D);
    const float var = fmaxf(s2 * (1.0f / D) - md * md, 0.f);
    const float mean = bf16r(shift + md);
    const float den = bf16r(sqrtf(bf16r(bf16r(var) + 1e-5f)));
    return make_float2(mean, __frcp_rn(den));
}
__device__ __forceinline__ float ln_norm(float x, float2 st) { return bf16r(bf16r(x - st.x) * st.y); }
__device__ __forceinline__ float modulate(float xn, float g1p, float shift) { return bf16r(bf16r(xn * g1p) + shift); }

template <int LO, int HI>
__device__ __forceinline__ void init_barriers(uint32_t bars) {
#pragma unroll
    for (int i = LO; i < HI; i++)
        mbar_init(bars + i * 8, i < B_EMPTY ? 1 : i < B_EMPTY + MAXT ? 4 : i < B_AFREE ? 8 : i == B_AFREE ? 8 : i == B_MODFREE ? 10 : i == B_GATES ? 2 : 1);
}

struct Maps { CUtensorMap mod, wq, k, v, wo, w1, w2; };
struct Ptrs { const void *wq, *v, *wo, *w1, *w2; };

__global__ void __launch_bounds__(NTHREADS, 1)
adaln_decode_kernel(const __grid_constant__ Maps maps, const __grid_constant__ Ptrs ptrs, const __nv_bfloat16* __restrict__ kbase,
                    const __nv_bfloat16* __restrict__ gmod,
                    const __nv_bfloat16* __restrict__ gx,
                    const __nv_bfloat16* __restrict__ gc, __nv_bfloat16* __restrict__ gout) {
    extern __shared__ __align__(1024) unsigned char smem_raw[];
    const uint32_t sm = (uint32_t)__cvta_generic_to_shared(smem_raw);
    const uint32_t bars = sm + O_BAR;
    const int tid = threadIdx.x, warp = tid >> 5, lane = tid & 31;
    uint32_t j;
    asm("mov.u32 %0, %%cluster_ctarank;" : "=r"(j));
    const int h = blockIdx.x / CS;
    const int nt = j < 4 ? 11 : 10;
    const int tile0 = j < 4 ? 11 * j : 44 + 10 * (j - 4);
#define BAR(i) (bars + (i) * 8)

    if (warp == NCW) {
        uint64_t pol;
        asm volatile("createpolicy.fractional.L2::evict_first.b64 %0, 1.0;" : "=l"(pol));
        if (lane == 0) PROF1(0);
        const uint32_t tstart = gtime32();
        if (lane == 0) {
            init_barriers<B_MODA, B_K>(bars);
            asm volatile("fence.mbarrier_init.release.cluster;" ::: "memory");
            mbar_expect_tx(BAR(B_MODA), SZ_MOD);
            tma2d(sm + O_MODA, &maps.mod, (h & 1) * D + 96 * j, (h >> 1) * 72, BAR(B_MODA), pol);
#pragma unroll
            for (int i = 0; i < NFIRST; i++) {
                mbar_expect_tx(BAR(B_WQ + i), SZ_WQ);
                tma3d(sm + O_WQ + i * SZ_WQ, &maps.wq, 0, 96 * j + i * 32, h * 4, BAR(B_WQ + i), pol);
            }
            PROF1(18);
        }
        __syncwarp();
        bar_arrive(0, NCT + 32);
        asm volatile("barrier.cluster.arrive.relaxed.aligned;" ::: "memory");
        bar_sync(3, 128 + MONW);
        if (lane != 0) return;
        uint32_t qm = 0, q0 = NFIRST > 2 ? BAR(B_WQ + NFIRST - 4) : 0, q1 = NFIRST > 1 ? BAR(B_WQ + NFIRST - 3) : 0,
                 q2 = NFIRST > 0 ? BAR(B_WQ + NFIRST - 2) : 0, q3 = BAR(B_WQ + NFIRST - 1);
#define MON() do {} while (0)
#define PACE(bytes_all) {}
#define STAGE_BEGIN(depth, bar_, bytes_all) \
        { const uint32_t w_ = (depth) == 5 ? qm : (depth) == 4 ? q0 : (depth) == 3 ? q1 : q2; if (w_) mbar_wait(w_); qm = q0; q0 = q1; q1 = q2; q2 = q3; q3 = (bar_); PACE(bytes_all); }
        const int cb = h * CS + j;
#pragma unroll 1
        for (int i = NFIRST; i < 3; i++) {
            const uint32_t b = BAR(B_WQ + i);
            STAGE_BEGIN(DEPTH_A, b, D * 4096 * 2 / 3);
            mbar_expect_tx(b, SZ_WQ);
            tma3d(sm + O_WQ + i * SZ_WQ, &maps.wq, 0, 96 * j + i * 32, h * 4, b, pol);
            MON();
        }
        asm volatile("prefetch.tensormap [%0];" ::"l"(&maps.k) : "memory");
#pragma unroll 1
        for (int i = 0; i < 2; i++) {
            const uint32_t b = BAR(B_MODB + i);
            STAGE_BEGIN(DEPTH_A, b, D * 4 * D * 2 / 2);
            mbar_expect_tx(b, SZ_MOD);
            tma2d(sm + O_MODB + i * SZ_MOD, &maps.mod, (2 + (h & 3)) * D + 96 * j, (h >> 2) * 144 + i * 72, b, pol);
            MON();
        }
        {
            const int row0 = h * SK + (SK - WINDOW) + tile0 * 64;
            int slot = 0;
#pragma unroll 1
            for (int n = 0; n < 2 * nt; n++) {
                const bool isv = n >= nt;
                const int t = isv ? n - nt : n;
                const uint32_t b = BAR((isv ? B_V : B_K) + t), dst = sm + slot_off(slot);
                const CUtensorMap* m = isv ? &maps.v : &maps.k;
                STAGE_BEGIN(DEPTH_KV, b, (nt == 11 ? NKV * WINDOW * DH * 4 / 22 : NKV * WINDOW * DH * 4 / 20));
                if (n == NRING) mbar_wait(BAR(B_MODFREE));
                if (n >= NSLOT) { const int pn = n - NSLOT; mbar_wait(BAR(B_EMPTY + (pn < nt ? pn : MAXT + pn - nt))); }
                mbar_expect_tx(b, SZ_KV);
                tma2d(dst, m, 0, row0 + t * 64, b, pol);
                tma2d(dst + 8192, m, 64, row0 + t * 64, b, pol);
                MON();
                slot = slot == NSLOT - 1 ? 0 : slot + 1;
                if (n == 0) PROF1(22);
                if (n == nt) PROF1(1);
                if (n == 3) asm volatile("prefetch.tensormap [%0];" ::"l"(&maps.v) : "memory");
                if (n == nt + 3) {
                    asm volatile("prefetch.tensormap [%0];" ::"l"(&maps.wo) : "memory");
                    asm volatile("prefetch.tensormap [%0];" ::"l"(&maps.w1) : "memory");
                    asm volatile("prefetch.tensormap [%0];" ::"l"(&maps.w2) : "memory");
                }
            }
        }
#pragma unroll 1
        for (int i = 0; i < 4; i++) {
            const uint32_t b = BAR(B_WO + i);
            STAGE_BEGIN(DEPTH_WO, b, D * 4096 * 2 / 4);
            if (i == 0) { mbar_wait(BAR(B_AFREE)); mbar_wait(BAR(B_MODFREE)); PROF1(2); }
            mbar_expect_tx(b, SZ_WO);
            tma2d(sm + O_WO + i * SZ_WO, &maps.wo, 96 * j, h * 256 + i * 64, b, pol);
            MON();
        }
#pragma unroll 1
        for (int i = 0; i < 4; i++) {
            const uint32_t b = BAR(B_W1 + i);
            STAGE_BEGIN(DEPTH_W1, b, D * FF * 2 / 4);
            if (i == 0) {
                mbar_wait(BAR(B_EMPTY + MAXT + 14 - nt));
                mbar_wait(BAR(B_EMPTY + MAXT + 15 - nt));
            }
            if (i == 2) mbar_wait(BAR(B_EMPTY + MAXT + nt - 1));
            mbar_expect_tx(b, SZ_W1);
            tma2d(sm + (i < 2 ? O_W1A + i * SZ_W1 : O_W1B + (i - 2) * SZ_W1), &maps.w1, cb * 48, i * 144, b, pol);
            MON();
        }
#pragma unroll 1
        for (int i = 0; i < 3; i++) {
            const uint32_t b = BAR(B_W2 + i);
            STAGE_BEGIN(DEPTH_W2, b, D * FF * 2 / 3);
            mbar_expect_tx(b, SZ_W2);
            tma3d(sm + O_W2 + i * SZ_W2, &maps.w2, 0, 0, cb * 48 + i * 16, b, pol);
            MON();
        }
        PROF1(3);
#undef STAGE_BEGIN
#undef MON
        asm volatile("barrier.cluster.wait;" ::: "memory");
        return;
    }

    const int g = lane >> 2, t4 = lane & 3;
    const int r7 = lane & 7, lg = lane >> 3;
    uint4* const a1_out = g_scr.a1 + ((((h & 1) * 6 + j) * 6) * 8 + (h >> 1)) * 8;
    uint4* const a2_out = g_scr.a2 + ((((h & 3) * 6 + j) * 6) * 4 + (h >> 2)) * 8;
    uint4* const c1_out = g_scr.c1 + ((j * 6) * 16 + h) * 8;
    uint4* const d1_out = g_scr.d1 + ((j * 6) * 16 + h) * 8;

    uint32_t xv = 0, cv = 0;
    if (warp >= 9) {
        if (lane == 0) {
            if (warp == 9) init_barriers<B_K, B_EMPTY>(bars);
            else if (warp == 10) init_barriers<B_EMPTY, B_AFREE>(bars);
            else {
                init_barriers<B_AFREE, NBAR>(bars);
                mbar_expect_tx(BAR(B_XQ), CS * 1024);
                mbar_expect_tx(BAR(B_XB), CS * 1040);
                mbar_expect_tx(BAR(B_XC), CS * 384);
                mbar_expect_tx(BAR(B_XG), CS * 768);
                mbar_expect_tx(BAR(B_XD), CS * 384);
            }
            asm volatile("fence.mbarrier_init.release.cluster;" ::: "memory");
        }
        __syncwarp();
        bar_arrive(3, 128 + MONW);
    } else {
        xv = __ldg(reinterpret_cast<const uint32_t*>(gx) + tid);
        cv = __ldg(reinterpret_cast<const uint32_t*>(gc) + tid);
    }
    uint32_t xall[9];
    uint32_t xc0 = 0, xc1 = 0;
    if (warp < 6) {
#pragma unroll
        for (int i = 0; i < 9; i++) xall[i] = __ldg(reinterpret_cast<const uint32_t*>(gx) + lane + 32 * i);
        xc0 = __ldg(reinterpret_cast<const unsigned short*>(gx) + 96 * j + warp * 16 + r7);
        xc1 = __ldg(reinterpret_cast<const unsigned short*>(gx) + 96 * j + warp * 16 + r7 + 8);
    }
    asm volatile("barrier.cluster.arrive.relaxed.aligned;" ::: "memory");
    uint32_t epoch = 0;
    if (tid == 288) epoch = *(volatile unsigned*)&g_scr.epoch;
    if (t4 == 0) {
        if (warp < 6) st_msg(a1_out + warp * 64 + g, 0.f, 0.f, 0);
        else if (warp >= 8) {
            st_msg(a2_out + (warp - 8) * 32 + g, 0.f, 0.f, 0);
            if (warp < 10) st_msg(a2_out + (warp - 4) * 32 + g, 0.f, 0.f, 0);
        }
    }
    if (tid < 288) {
        stsf2(sm + O_XS + tid * 8, __uint_as_float(xv << 16), __uint_as_float(xv & 0xffff0000u));
        const float c0 = silu_bf16(__uint_as_float(cv << 16)), c1 = silu_bf16(__uint_as_float(cv & 0xffff0000u));
        sts32(sm + O_SC + tid * 4, (__float_as_uint(c0) >> 16) | (__float_as_uint(c1) & 0xffff0000u));
    }
    if (tid == 288) sts32(sm + O_TAG, epoch + 1);
    float xn0 = 0.f, xn1 = 0.f;
    if (warp < 6) {
        float xr[18];
#pragma unroll
        for (int i = 0; i < 9; i++) { xr[2 * i] = __uint_as_float(xall[i] << 16); xr[2 * i + 1] = __uint_as_float(xall[i] & 0xffff0000u); }
        const float2 st = ln_stats(xr, __shfl_sync(0xffffffffu, xr[0], 0));
        xn0 = ln_norm(__uint_as_float(xc0 << 16), st);
        xn1 = ln_norm(__uint_as_float(xc1 << 16), st);
    }
    if (warp == 0) PROF(21);
    bar_sync(0, NCT + 32);
    const uint32_t tag = lds32(sm + O_TAG);
    if (warp == 0) PROF(4);

    if (warp < 6) {
        float acc0[4] = {0.f, 0.f, 0.f, 0.f}, acc1[4] = {0.f, 0.f, 0.f, 0.f};
        const uint32_t va = sm + O_SC + ((h >> 1) * 72 + 2 * t4) * 2;
        mbar_wait(BAR(B_MODA));
        if (warp == 0) PROF(19);
        gemv_tile<P_MOD, 4>(acc0, acc1, gemv_addr<P_MOD>(sm + O_MODA, warp * 16, lane), va);
        {
            uint32_t a[2];
            ldsm2t(a, sm + O_MODA + (64 + r7) * P_MOD + (warp * 16 + 8 * (lg & 1)) * 2);
            mma8(acc0, a, lds32(va + 128));
        }
        if (t4 == 0) st_msg(a1_out + warp * 64 + g, acc0[0] + acc1[0], acc0[2] + acc1[2], tag);
        if (lane == 0) mbar_arrive(BAR(B_MODFREE));
        if (warp == 0) PROF(5);
        const uint4* in = g_scr.a1 + (j * 6 + warp) * 64 + lane;
        float2 sa, ca;
        gather_msgs2(in, in + 36 * 64, tag, sa, ca, sm);
        if (lg == 0) {
            const int c = warp * 16 + r7;
            sts_bf16(sm + O_HV + c * 2, modulate(xn0, bf16r(1.f + bf16r(ca.x)), bf16r(sa.x)));
            sts_bf16(sm + O_HV + (c + 8) * 2, modulate(xn1, bf16r(1.f + bf16r(ca.y)), bf16r(sa.y)));
        }
        if (warp == 0) PROF(6);
    }
    asm volatile("barrier.cluster.wait.aligned;" ::: "memory");

    if (warp < 8) {
        bar_sync(1, 256);
        float a00[4] = {0.f, 0.f, 0.f, 0.f}, a01[4] = {0.f, 0.f, 0.f, 0.f};
        float a10[4] = {0.f, 0.f, 0.f, 0.f}, a11[4] = {0.f, 0.f, 0.f, 0.f};
        const uint32_t va = sm + O_HV + 4 * t4;
        const uint32_t a_off = (warp >> 1) * 4096 + (r7 + 8 * (lg >> 1)) * 128 + (((4 * (warp & 1) + (lg & 1)) ^ r7) << 4);
#pragma unroll
        for (int i = 0; i < 3; i++) {
            mbar_wait(BAR(B_WQ + i));
            if (i == 2 && warp == 4) PROF(20);
#pragma unroll
            for (int k2 = 0; k2 < 2; k2++) {
                const int ks = 2 * i + k2;
                const uint32_t b0 = lds32(va + ks * 32), b1 = lds32(va + ks * 32 + 16);
                uint32_t a[4];
                ldsm4t(a, sm + O_WQ + i * SZ_WQ + k2 * 2048 + a_off);
                if (k2) mma16(a01, a, b0, b1); else mma16(a00, a, b0, b1);
                ldsm4t(a, sm + O_WQ + i * SZ_WQ + k2 * 2048 + (a_off ^ 32));
                if (k2) mma16(a11, a, b0, b1); else mma16(a10, a, b0, b1);
            }
        }
        const uint32_t dst = sm + O_QBUF + j * 1024 + (warp * 8 + g) * 16;
        const float v0 = a00[0] + a01[0], v1 = a00[2] + a01[2], v2 = a10[0] + a11[0], v3 = a10[2] + a11[2];
        st_async4(mapa(dst, t4), v0, v1, v2, v3, mapa(BAR(B_XQ), t4));
        if (t4 < 2) st_async4(mapa(dst, t4 + 4), v0, v1, v2, v3, mapa(BAR(B_XQ), t4 + 4));
        if (lane == 0) mbar_arrive(BAR(B_AFREE));
        mbar_wait_cluster(BAR(B_XQ));
        float q = 0.f;
#pragma unroll
        for (int s = 0; s < CS; s++) q += ldsf(sm + O_QBUF + s * 1024 + tid * 4);
        const int e = tid & 3;
        const int n = warp * 32 + (e >> 1) * 16 + g + 8 * (e & 1);
        sts_bf16(sm + O_QV + n * 2, q);
    }
    if (warp >= 8) {
        mbar_wait(BAR(B_MODB));
        mbar_wait(BAR(B_MODB + 1));
        const uint32_t va = sm + O_SC + ((h >> 2) * 144 + 2 * t4) * 2;
        for (int l = warp - 8; l < 6; l += 4) {
            float acc0[4] = {0.f, 0.f, 0.f, 0.f}, acc1[4] = {0.f, 0.f, 0.f, 0.f};
            gemv_tile<P_MOD, 9>(acc0, acc1, gemv_addr<P_MOD>(sm + O_MODB, l * 16, lane), va);
            if (t4 == 0) st_msg(a2_out + l * 32 + g, acc0[0] + acc1[0], acc0[2] + acc1[2], tag);
        }
        __syncwarp();
        if (lane == 0) mbar_arrive(BAR(B_MODFREE));
    }

    bar_sync(2, NCT);
    if (warp == 0) PROF(7);
    uint32_t qb[16];
#pragma unroll
    for (int ks = 0; ks < 8; ks++) {
        const uint32_t a = sm + O_QV + ((g & 1) * 128 + ks * 16 + 2 * t4) * 2;
        qb[2 * ks] = lds32(a);
        qb[2 * ks + 1] = lds32(a + 16);
    }

    float sc[4];
    {
        const int grp = warp >> 2, mi = lg;
        const uint32_t a_off = (16 * (warp & 3) + r7 + 8 * (mi & 1)) * 128 + (((mi >> 1) ^ r7) << 4);
        float mx = -INFINITY;
#pragma unroll
        for (int it = 0; it < 4; it++) {
            const int t = grp + 3 * it;
            sc[it] = -INFINITY;
            if (t < nt) {
                mbar_wait(BAR(B_K + t));
                const uint32_t base = sm + slot_off(t % NSLOT);
                float c0[4] = {0.f, 0.f, 0.f, 0.f}, c1[4] = {0.f, 0.f, 0.f, 0.f};
#pragma unroll
                for (int ks = 0; ks < 8; ks++) {
                    uint32_t a[4];
                    ldsm4(a, base + (ks >> 2) * 8192 + (a_off ^ ((ks & 3) << 5)));
                    if (ks & 1) mma16(c1, a, qb[2 * ks], qb[2 * ks + 1]); else mma16(c0, a, qb[2 * ks], qb[2 * ks + 1]);
                }
                __syncwarp();
                if (lane == 0) mbar_arrive(BAR(B_EMPTY + t));
                const float v = t4 == 0 ? c0[0] + c1[0] : t4 == 1 ? c0[1] + c1[1] : t4 == 2 ? c0[2] + c1[2] : c0[3] + c1[3];
                sc[it] = bf16r(bf16r(v) * 0.08838834764831845f);
                mx = fmaxf(mx, sc[it]);
            }
        }
        mx = fmaxf(mx, __shfl_xor_sync(0xffffffffu, mx, 2));
        mx = fmaxf(mx, __shfl_xor_sync(0xffffffffu, mx, 4));
        mx = fmaxf(mx, __shfl_xor_sync(0xffffffffu, mx, 8));
        mx = fmaxf(mx, __shfl_xor_sync(0xffffffffu, mx, 16));
        if (lane < 2) stsf(sm + O_WMAX + (warp * 2 + lane) * 4, mx);
    }
    bar_sync(2, NCT);
    if (warp == 0) PROF(8);
    float cta_max;
    {
        const int hd = t4 & 1, grp = warp >> 2;
        float m = -INFINITY;
#pragma unroll
        for (int w = 0; w < NCW; w++) m = fmaxf(m, ldsf(sm + O_WMAX + (w * 2 + hd) * 4));
        cta_max = m;
        float l = 0.f;
#pragma unroll
        for (int it = 0; it < 4; it++) {
            const int t = grp + 3 * it;
            if (t < nt) {
                const float p = __expf(sc[it] - m);
                l += p;
                sts_bf16(sm + O_PV + (hd * PV_PITCH + t * 64 + 16 * (warp & 3) + g + 8 * (t4 >> 1)) * 2, p);
            }
        }
        l += __shfl_xor_sync(0xffffffffu, l, 2);
        l += __shfl_xor_sync(0xffffffffu, l, 4);
        l += __shfl_xor_sync(0xffffffffu, l, 8);
        l += __shfl_xor_sync(0xffffffffu, l, 16);
        if (lane < 2) stsf(sm + O_WL + (warp * 2 + lane) * 4, l);
    }
    if (warp < 6 && t4 == 0) {
        st_msg(c1_out + warp * 128 + g, 0.f, 0.f, 0);
        st_msg(d1_out + warp * 128 + g, 0.f, 0.f, 0);
    }
    bar_sync(2, NCT);

    if (warp >= 8) {
        const int m = warp - 8;
#pragma unroll 1
        for (int l = 0; l < 6; l++) {
            const float2 v = gather_msgs<1>(g_scr.a2 + ((m * 6 + j) * 6 + l) * 32 + lane, 0, tag);
            float a = bf16r(v.x), b = bf16r(v.y);
            if (m == 0 || m == 3) {
                if (lg == 0) stsf2(sm + (m == 0 ? O_GA : O_GB) + (l * 8 + r7) * 8, a, b);
            } else {
                if (m == 2) { a = bf16r(1.f + a); b = bf16r(1.f + b); }
                const uint32_t dst = sm + (m == 1 ? O_SB : O_G1P) + ((j * 6 + l) * 8 + r7) * 8;
                st_async2(mapa(dst, lg), a, b, mapa(BAR(B_XG), lg));
                if (lg < 2) st_async2(mapa(dst, lg + 4), a, b, mapa(BAR(B_XG), lg + 4));
            }
        }
        __syncwarp();
        if (lane == 0 && (m == 0 || m == 3)) mbar_arrive(BAR(B_GATES));
        if (warp == 8) {
            const float m0 = __shfl_sync(0xffffffffu, cta_max, 0), m1 = __shfl_sync(0xffffffffu, cta_max, 1);
            float l0 = 0.f, l1 = 0.f;
#pragma unroll
            for (int w = 0; w < NCW; w++) { const float2 v = ldsf2(sm + O_WL + w * 8); l0 += v.x; l1 += v.y; }
            if (lane < CS) st_async4(mapa(sm + O_MLBUF + j * 16, lane), m0, m1, l0, l1, mapa(BAR(B_XB), lane));
        }
    } else {
        const int mi = lg;
        const uint32_t a_off = (warp >> 2) * 8192 + (r7 + 8 * (mi >> 1)) * 128 + (((2 * (warp & 3) + (mi & 1)) ^ r7) << 4);
        const uint32_t pa = sm + O_PV + ((g & 1) * PV_PITCH + 2 * t4) * 2;
        float c0[4] = {0.f, 0.f, 0.f, 0.f}, c1[4] = {0.f, 0.f, 0.f, 0.f};
#pragma unroll 1
        for (int t = 0; t < nt; t++) {
            uint32_t b[8];
#pragma unroll
            for (int ks = 0; ks < 4; ks++) { b[2 * ks] = lds32(pa + (t * 64 + ks * 16) * 2); b[2 * ks + 1] = lds32(pa + (t * 64 + ks * 16) * 2 + 16); }
            mbar_wait(BAR(B_V + t));
            const uint32_t base = sm + slot_off((nt + t) % NSLOT) + a_off;
#pragma unroll
            for (int ks = 0; ks < 4; ks++) {
                uint32_t a[4];
                ldsm4t(a, base + ks * 2048);
                if (ks & 1) mma16(c1, a, b[2 * ks], b[2 * ks + 1]); else mma16(c0, a, b[2 * ks], b[2 * ks + 1]);
            }
            __syncwarp();
            if (lane == 0) mbar_arrive(BAR(B_EMPTY + MAXT + t));
        }
        if (warp == 0) PROF(9);
        const uint32_t dst = sm + O_OBUF + j * 1024 + (warp * 8 + g) * 16;
        const float v0 = c0[0] + c1[0], v1 = c0[1] + c1[1], v2 = c0[2] + c1[2], v3 = c0[3] + c1[3];
        st_async4(mapa(dst, t4), v0, v1, v2, v3, mapa(BAR(B_XB), t4));
        if (t4 < 2) st_async4(mapa(dst, t4 + 4), v0, v1, v2, v3, mapa(BAR(B_XB), t4 + 4));
        mbar_wait_cluster(BAR(B_XB));
        {
            const int e = tid & 3, hd = e & 1;
            float ms[CS], ls[CS], M = -INFINITY;
#pragma unroll
            for (int s = 0; s < CS; s++) {
                const float4 v = ldsf4(sm + O_MLBUF + s * 16);
                ms[s] = hd ? v.y : v.x; ls[s] = hd ? v.w : v.z;
                M = fmaxf(M, ms[s]);
            }
            float L = 0.f, o = 0.f;
#pragma unroll
            for (int s = 0; s < CS; s++) {
                const float w = __expf(ms[s] - M);
                L = fmaf(w, ls[s], L);
                o = fmaf(w, ldsf(sm + O_OBUF + s * 1024 + tid * 4), o);
            }
            const int n = hd * 128 + warp * 16 + g + 8 * (e >> 1);
            sts_bf16(sm + O_OV + n * 2, o / L);
        }
        bar_sync(1, 256);
        if (warp == 0) PROF(10);
        if (warp < 6) {
            float acc0[4] = {0.f, 0.f, 0.f, 0.f}, acc1[4] = {0.f, 0.f, 0.f, 0.f};
            const uint32_t va = sm + O_OV + 4 * t4;
#pragma unroll
            for (int i = 0; i < 4; i++) {
                mbar_wait(BAR(B_WO + i));
                gemv_tile<P_WO, 4>(acc0, acc1, gemv_addr<P_WO>(sm + O_WO + i * SZ_WO, warp * 16, lane), va + i * 128);
            }
            if (t4 == 0) st_msg(c1_out + warp * 128 + g, acc0[0] + acc1[0], acc0[2] + acc1[2], tag);
            if (warp == 0) PROF(11);
            const int c = 96 * j + warp * 16 + r7;
            const float x0 = ldsf(sm + O_XS + c * 4), x1 = ldsf(sm + O_XS + (c + 8) * 4);
            mbar_wait(BAR(B_GATES));
            const float2 ga = ldsf2(sm + O_GA + (warp * 8 + r7) * 8);
            const float2 at = gather_msgs<4>(g_scr.c1 + (j * 6 + warp) * 128 + lane, 32, tag);
            const float y0 = bf16r(x0 + bf16r(ga.x * bf16r(at.x))), y1 = bf16r(x1 + bf16r(ga.y * bf16r(at.y)));
            const uint32_t dst2 = sm + O_X2 + ((j * 6 + warp) * 8 + r7) * 8;
            st_async2(mapa(dst2, lg), y0, y1, mapa(BAR(B_XC), lg));
            if (lg < 2) st_async2(mapa(dst2, lg + 4), y0, y1, mapa(BAR(B_XC), lg + 4));
            if (warp == 0) PROF(12);
        }
    }

    mbar_wait_cluster(BAR(B_XG));
    mbar_wait_cluster(BAR(B_XC));
    {
        float xr[18];
#pragma unroll
        for (int i = 0; i < 9; i++) { const float2 v = ldsf2(sm + O_X2 + (lane + 32 * i) * 8); xr[2 * i] = v.x; xr[2 * i + 1] = v.y; }
        const float2 st = ln_stats(xr, ldsf(sm + O_X2));
        if (tid < 288) {
            const float2 x = ldsf2(sm + O_X2 + tid * 8), g1 = ldsf2(sm + O_G1P + tid * 8), sb = ldsf2(sm + O_SB + tid * 8);
            const int c = (tid >> 3) * 16 + (tid & 7);
            sts_bf16(sm + O_H2 + c * 2, modulate(ln_norm(x.x, st), g1.x, sb.x));
            sts_bf16(sm + O_H2 + (c + 8) * 2, modulate(ln_norm(x.y, st), g1.y, sb.y));
        }
    }
    bar_sync(2, NCT);
    if (warp == 0) PROF(13);

    {
        const int mt = warp % 3, kq = warp / 3;
        float acc0[4] = {0.f, 0.f, 0.f, 0.f}, acc1[4] = {0.f, 0.f, 0.f, 0.f};
        const uint32_t tile = sm + (kq < 2 ? O_W1A + kq * SZ_W1 : O_W1B + (kq - 2) * SZ_W1);
        mbar_wait(BAR(B_W1 + kq));
        gemv_tile<P_W1, 9>(acc0, acc1, gemv_addr<P_W1>(tile, mt * 16, lane), sm + O_H2 + (kq * 144 + 2 * t4) * 2);
        if (t4 == 0) {
            stsf(sm + O_RED1 + (kq * 48 + mt * 16 + g) * 4, acc0[0] + acc1[0]);
            stsf(sm + O_RED1 + (kq * 48 + mt * 16 + g + 8) * 4, acc0[2] + acc1[2]);
        }
    }
    bar_sync(2, NCT);
    if (warp == 0) PROF(14);

    {
        const int pi = lane < 24 ? lane : 0;
        float2 s = ldsf2(sm + O_RED1 + pi * 8);
#pragma unroll
        for (int q = 1; q < 4; q++) { const float2 v = ldsf2(sm + O_RED1 + q * 192 + pi * 8); s.x += v.x; s.y += v.y; }
        const float u0 = silu_bf16(bf16r(s.x)), u1 = silu_bf16(bf16r(s.y));
        const uint32_t pk = (__float_as_uint(u0) >> 16) | (__float_as_uint(u1) & 0xffff0000u);
        uint32_t b[6];
#pragma unroll
        for (int ks = 0; ks < 3; ks++) {
            b[2 * ks] = __shfl_sync(0xffffffffu, pk, 8 * ks + t4);
            b[2 * ks + 1] = __shfl_sync(0xffffffffu, pk, 8 * ks + 4 + t4);
        }
        float acc[3][4];
        const uint32_t a_addr = gemv_addr<P_W2>(sm + O_W2 + (warp >> 2) * 400, (warp & 3) * 48, lane);
#pragma unroll
        for (int mt = 0; mt < 3; mt++) acc[mt][0] = acc[mt][1] = acc[mt][2] = acc[mt][3] = 0.f;
#pragma unroll
        for (int ks = 0; ks < 3; ks++) {
            mbar_wait(BAR(B_W2 + ks));
#pragma unroll
            for (int mt = 0; mt < 3; mt++) {
                uint32_t a[4];
                ldsm4t(a, a_addr + ks * SZ_W2 + mt * 32);
                mma16(acc[mt], a, b[2 * ks], b[2 * ks + 1]);
            }
        }
        if (t4 < 3) {
            const float v0 = t4 == 0 ? acc[0][0] : t4 == 1 ? acc[1][0] : acc[2][0];
            const float v1 = t4 == 0 ? acc[0][2] : t4 == 1 ? acc[1][2] : acc[2][2];
            const int dstj = warp >> 1;
            const uint32_t dst = sm + O_D0 + ((j * 6 + (warp & 1) * 3 + t4) * 8 + g) * 8;
            st_async2(mapa(dst, dstj), v0, v1, mapa(BAR(B_XD), dstj));
        }
    }
    if (warp == 0) PROF(15);

    if (warp < 6) {
        mbar_wait_cluster(BAR(B_XD));
        if (t4 == 0) {
            float2 s = ldsf2(sm + O_D0 + (warp * 8 + g) * 8);
#pragma unroll
            for (int q = 1; q < CS; q++) { const float2 v = ldsf2(sm + O_D0 + ((q * 6 + warp) * 8 + g) * 8); s.x += v.x; s.y += v.y; }
            st_msg(d1_out + warp * 128 + g, s.x, s.y, tag);
        }
        if (warp == 0) PROF(16);
        if (warp == h) {
            const float2 x2 = ldsf2(sm + O_X2 + ((j * 6 + warp) * 8 + r7) * 8);
            const float2 gb = ldsf2(sm + O_GB + (warp * 8 + r7) * 8);
            const float2 y = gather_msgs<4>(g_scr.d1 + (j * 6 + warp) * 128 + lane, 32, tag);
            if (lg == 0) {
                const int c = 96 * j + warp * 16 + r7;
                gout[c] = __float2bfloat16_rn(x2.x + bf16r(gb.x * bf16r(y.x)));
                gout[c + 8] = __float2bfloat16_rn(x2.y + bf16r(gb.y * bf16r(y.y)));
            }
            if (blockIdx.x == 0 && lane == 0) *(volatile unsigned*)&g_scr.epoch = tag;
            PROF(17);
        }
    }
#undef BAR
}

typedef CUresult (*EncodeTiledFn)(CUtensorMap*, CUtensorMapDataType, cuuint32_t, void*, const cuuint64_t*,
                                  const cuuint64_t*, const cuuint32_t*, const cuuint32_t*, CUtensorMapInterleave,
                                  CUtensorMapSwizzle, CUtensorMapL2promotion, CUtensorMapFloatOOBfill);

void encode2d(EncodeTiledFn enc, CUtensorMap* m, const void* base, uint64_t rows, uint64_t cols, uint32_t box_cols,
              uint32_t box_rows, CUtensorMapSwizzle swz) {
    cuuint64_t dims[2] = {cols, rows};
    cuuint64_t strides[1] = {cols * 2};
    cuuint32_t box[2] = {box_cols, box_rows};
    cuuint32_t es[2] = {1, 1};
    enc(m, CU_TENSOR_MAP_DATA_TYPE_BFLOAT16, 2, const_cast<void*>(base), dims, strides, box, es,
        CU_TENSOR_MAP_INTERLEAVE_NONE, swz, CU_TENSOR_MAP_L2_PROMOTION_NONE, CU_TENSOR_MAP_FLOAT_OOB_FILL_NONE);
}

void encode3d(EncodeTiledFn enc, CUtensorMap* m, const void* base, uint64_t d0, uint64_t d1, uint64_t d2, uint64_t s1,
              uint64_t s2, uint32_t b0, uint32_t b1, uint32_t b2, CUtensorMapSwizzle swz) {
    cuuint64_t dims[3] = {d0, d1, d2};
    cuuint64_t strides[2] = {s1, s2};
    cuuint32_t box[3] = {b0, b1, b2};
    cuuint32_t es[3] = {1, 1, 1};
    CUresult r = enc(m, CU_TENSOR_MAP_DATA_TYPE_BFLOAT16, 3, const_cast<void*>(base), dims, strides, box, es,
        CU_TENSOR_MAP_INTERLEAVE_NONE, swz, CU_TENSOR_MAP_L2_PROMOTION_NONE, CU_TENSOR_MAP_FLOAT_OOB_FILL_NONE);
    (void)r;
}

}

extern "C" void kernel_launch(void* const* d_in, const int* in_sizes, int n_in, void* d_out, int out_size) {
    (void)in_sizes; (void)n_in; (void)out_size;
    void* fn = nullptr;
    cudaDriverEntryPointQueryResult qr;
    cudaGetDriverEntryPoint("cuTensorMapEncodeTiled", &fn, cudaEnableDefault, &qr);
    EncodeTiledFn enc = (EncodeTiledFn)fn;
    Maps maps;
    encode2d(enc, &maps.mod, d_in[9], D, 6 * D, 104, 72, CU_TENSOR_MAP_SWIZZLE_NONE);
    encode3d(enc, &maps.wq, d_in[3], 64, D, 64, 4096 * 2, 128, 64, 32, 4, CU_TENSOR_MAP_SWIZZLE_128B);
    encode2d(enc, &maps.k, d_in[1], (uint64_t)NKV * SK, DH, 64, 64, CU_TENSOR_MAP_SWIZZLE_128B);
    encode2d(enc, &maps.v, d_in[2], (uint64_t)NKV * SK, DH, 64, 64, CU_TENSOR_MAP_SWIZZLE_128B);
    encode2d(enc, &maps.wo, d_in[4], 4096, D, 104, 64, CU_TENSOR_MAP_SWIZZLE_NONE);
    encode2d(enc, &maps.w1, d_in[6], D, FF, 56, 144, CU_TENSOR_MAP_SWIZZLE_NONE);
    encode3d(enc, &maps.w2, d_in[7], 192, 3, FF, 384, D * 2, 200, 3, 16, CU_TENSOR_MAP_SWIZZLE_NONE);

    cudaFuncSetAttribute(adaln_decode_kernel, cudaFuncAttributeMaxDynamicSharedMemorySize, SMEM_BYTES);
    cudaLaunchConfig_t cfg = {};
    cfg.gridDim = dim3(NKV * CS);
    cfg.blockDim = dim3(NTHREADS);
    cfg.dynamicSmemBytes = SMEM_BYTES;
    cfg.stream = cudaStreamPerThread;
    cudaLaunchAttribute at[1];
    at[0].id = cudaLaunchAttributeClusterDimension;
    at[0].val.clusterDim.x = CS;
    at[0].val.clusterDim.y = 1;
    at[0].val.clusterDim.z = 1;
    cfg.attrs = at;
    cfg.numAttrs = 1;
    Ptrs ptrs = {d_in[3], d_in[2], d_in[4], d_in[6], d_in[7]};
    cudaLaunchKernelEx(&cfg, adaln_decode_kernel, maps, ptrs, (const __nv_bfloat16*)d_in[1], (const __nv_bfloat16*)d_in[9], (const __nv_bfloat16*)d_in[0], (const __nv_bfloat16*)d_in[8],
                       (__nv_bfloat16*)d_out);
}
```

```cpp
#include <cuda.h>
#include <cuda_bf16.h>
#include <cuda_runtime.h>
#include <stdint.h>

namespace {

constexpr int D = 576, FF = 4608, NKV = 16, SK = 65536, WINDOW = 4096, DH = 128;
constexpr int CS = 6;
constexpr int NCW = 12;
constexpr int NCT = NCW * 32;
constexpr int MONW = 0;
constexpr int NTHREADS = NCT + 32 + MONW;
constexpr int MAXT = 11;

#define DEPTH_A 4
#define DEPTH_KV 4
#define DEPTH_WO 4
#define DEPTH_W1 4
#define DEPTH_W2 4
#define PACE_GBPS 3200
#define PACE_A PACE_GBPS
#define PACE_WO 3400
#define PACE_W1 2250
#define PACE_W2 2900
#define W2_EARLY 0
#define PACE_W2E PACE_W2
#define PACE_LEAD 0
#define TLB_WARM 0
#define PWAIT mbar_spin
#define POLL_SLEEP 0
#define PROMO_MOD 2
#define PROMO_WO 2
#define PROMO_W1 2
#define TMA_WARM 0
#define NFIRST 1
#define WQ_DELAY 0
#define KPREFETCH 0

constexpr int P_MOD = 208, P_WO = 208, P_W1 = 112, P_W2 = 1200;
constexpr int SZ_MOD = 72 * P_MOD, SZ_WQ = 32 * 512, SZ_KV = 64 * 256, SZ_WO = 64 * P_WO, SZ_W1 = 144 * P_W1,
              SZ_W2 = 16 * P_W2;
constexpr int O_WQ = 0, O_MODA = O_WQ + 3 * SZ_WQ, O_MODB = O_MODA + SZ_MOD;
constexpr int O_WO = 0, O_W1A = O_WO + 4 * SZ_WO;
constexpr int O_RING = 95 * 1024, NRING = 6, NSLOT = 8;
constexpr int O_XSLOT = O_RING - 2 * SZ_KV;
constexpr int O_W1B = O_RING, O_W2 = O_W1B + 2 * SZ_W1;
constexpr int O_MISC = O_RING + NRING * SZ_KV;
static_assert(O_MODB + 2 * SZ_MOD <= O_RING && O_W1A + 2 * SZ_W1 <= O_RING, "area A");
static_assert(O_W2 + 3 * SZ_W2 <= O_MISC, "ring");
static_assert(O_XSLOT >= O_MODA && O_XSLOT % 1024 == 0 && O_XSLOT >= O_WO + 4 * SZ_WO, "extra slots");
__device__ __forceinline__ uint32_t slot_off(int slot) { return slot < NRING ? O_RING + slot * SZ_KV : O_XSLOT + (slot - NRING) * SZ_KV; }
constexpr int O_QBUF = O_MISC;
constexpr int O_OBUF = O_QBUF + 6144;
constexpr int O_MLBUF = O_OBUF + 6144;
constexpr int O_X2 = O_MLBUF + 128;
constexpr int O_G1P = O_X2 + 2304;
constexpr int O_SB = O_G1P + 2304;
constexpr int O_D0 = O_SB + 2304;
constexpr int O_XS = O_D0 + 2304;
constexpr int O_SC = O_XS + 2304;
constexpr int O_HV = O_SC + 1152;
constexpr int O_QV = O_HV + 256;
constexpr int PV_PITCH = 712;
constexpr int O_PV = O_QV + 512;
constexpr int O_OV = O_PV + 2944;
constexpr int O_H2 = O_OV + 512;
constexpr int O_RED1 = O_H2 + 1152;
constexpr int O_GA = O_RED1 + 768;
constexpr int O_GB = O_GA + 384;
constexpr int O_WMAX = O_GB + 384;
constexpr int O_WL = O_WMAX + 128;
constexpr int O_TAG = O_WL + 112;
constexpr int O_BAR = O_WL + 128;
constexpr int B_MODA = 0, B_WQ = 1, B_MODB = 4, B_K = 6, B_V = B_K + MAXT, B_WO = B_V + MAXT, B_W1 = B_WO + 4,
              B_W2 = B_W1 + 4, B_EMPTY = B_W2 + 3  , B_AFREE = B_EMPTY + 2 * MAXT, B_MODFREE = B_AFREE + 1, B_XQ = B_MODFREE + 1,
              B_XB = B_XQ + 1, B_XC = B_XB + 1, B_XG = B_XC + 1, B_XD = B_XG + 1, B_GATES = B_XD + 1,
              NBAR = B_GATES + 1;
constexpr int SMEM_BYTES = O_BAR + NBAR * 8;
static_assert(SMEM_BYTES <= 232448, "smem");

struct alignas(128) Scratch {
    uint4 a1[2 * 6 * 6 * 8 * 8];
    uint4 a2[4 * 6 * 6 * 4 * 8];
    uint4 c1[6 * 6 * 16 * 8];
    uint4 d1[6 * 6 * 16 * 8];
    unsigned epoch;
};
__device__ Scratch g_scr;

#define PROF(i) do {} while (0)
#define PROF1(i) do {} while (0)

__device__ __forceinline__ void mbar_init(uint32_t bar, uint32_t cnt) {
    asm volatile("mbarrier.init.shared::cta.b64 [%0], %1;" ::"r"(bar), "r"(cnt) : "memory");
}
__device__ __forceinline__ void mbar_expect_tx(uint32_t bar, uint32_t bytes) {
    asm volatile("mbarrier.arrive.expect_tx.shared::cta.b64 _, [%0], %1;" ::"r"(bar), "r"(bytes) : "memory");
}
__device__ __forceinline__ void mbar_arrive(uint32_t bar) {
    asm volatile("mbarrier.arrive.shared::cta.b64 _, [%0];" ::"r"(bar) : "memory");
}
__device__ __forceinline__ void mbar_wait(uint32_t bar) {
    uint32_t ok;
    int n = 0;
    do {
        asm volatile("{\n.reg .pred p;\nmbarrier.try_wait.parity.shared::cta.b64 p, [%1], 0;\nselp.u32 %0, 1, 0, p;\n}"
                     : "=r"(ok) : "r"(bar) : "memory");
        if (++n > (1 << 22)) __trap();
    } while (!ok);
}
__device__ __forceinline__ void mbar_spin(uint32_t bar) {
    uint32_t ok;
    int n = 0;
    do {
        asm volatile("{\n.reg .pred p;\nmbarrier.test_wait.parity.shared::cta.b64 p, [%1], 0;\nselp.u32 %0, 1, 0, p;\n}"
                     : "=r"(ok) : "r"(bar) : "memory");
        if (++n > (1 << 24)) __trap();
    } while (!ok);
}
__device__ __forceinline__ void mbar_wait_cluster(uint32_t bar) {
    uint32_t ok;
    int n = 0;
    do {
        asm volatile("{\n.reg .pred p;\nmbarrier.try_wait.parity.acquire.cluster.shared::cta.b64 p, [%1], 0;\nselp.u32 %0, 1, 0, p;\n}"
                     : "=r"(ok) : "r"(bar) : "memory");
        if (++n > (1 << 22)) __trap();
    } while (!ok);
}
__device__ __forceinline__ uint32_t gtime32() { uint32_t t; asm volatile("mov.u32 %0, %%globaltimer_lo;" : "=r"(t)); return t; }
__device__ __forceinline__ void bar_sync(int id, int n) { asm volatile("bar.sync %0, %1;" ::"r"(id), "r"(n) : "memory"); }
__device__ __forceinline__ void bar_arrive(int id, int n) { asm volatile("bar.arrive %0, %1;" ::"r"(id), "r"(n) : "memory"); }
__device__ __forceinline__ void tma2d(uint32_t dst, const CUtensorMap* m, int c0, int c1, uint32_t bar, uint64_t pol) {
    asm volatile("cp.async.bulk.tensor.2d.shared::cluster.global.mbarrier::complete_tx::bytes.L2::cache_hint [%0], [%1, {%3, %4}], [%2], %5;"
                 ::"r"(dst), "l"(m), "r"(bar), "r"(c0), "r"(c1), "l"(pol) : "memory");
}
__device__ __forceinline__ void tma3d(uint32_t dst, const CUtensorMap* m, int c0, int c1, int c2, uint32_t bar, uint64_t pol) {
    asm volatile("cp.async.bulk.tensor.3d.shared::cluster.global.mbarrier::complete_tx::bytes.L2::cache_hint [%0], [%1, {%3, %4, %5}], [%2], %6;"
                 ::"r"(dst), "l"(m), "r"(bar), "r"(c0), "r"(c1), "r"(c2), "l"(pol) : "memory");
}
__device__ __forceinline__ void tma_touch(const void* p) {
    asm volatile("cp.async.bulk.prefetch.L2.global [%0], 16;" ::"l"(p) : "memory");
}
__device__ __forceinline__ uint32_t mapa(uint32_t addr, uint32_t rank) {
    uint32_t r;
    asm("mapa.shared::cluster.u32 %0, %1, %2;" : "=r"(r) : "r"(addr), "r"(rank));
    return r;
}
__device__ __forceinline__ void st_async4(uint32_t addr, float a, float b, float c, float d, uint32_t bar) {
    asm volatile("st.async.weak.shared::cluster.mbarrier::complete_tx::bytes.v4.f32 [%0], {%1,%2,%3,%4}, [%5];"
                 ::"r"(addr), "f"(a), "f"(b), "f"(c), "f"(d), "r"(bar) : "memory");
}
__device__ __forceinline__ void st_async2(uint32_t addr, float a, float b, uint32_t bar) {
    asm volatile("st.async.weak.shared::cluster.mbarrier::complete_tx::bytes.v2.f32 [%0], {%1,%2}, [%3];"
                 ::"r"(addr), "f"(a), "f"(b), "r"(bar) : "memory");
}
__device__ __forceinline__ void st_msg(uint4* p, float a, float b, uint32_t tag) {
    asm volatile("{\n.reg .b128 t;\n.reg .b64 lo, hi;\nmov.b64 lo, {%1,%2};\nmov.b64 hi, {%3,%3};\nmov.b128 t, {lo,hi};\n"
                 "st.relaxed.gpu.global.b128 [%0], t;\n}"
                 ::"l"(p), "r"(__float_as_uint(a)), "r"(__float_as_uint(b)), "r"(tag) : "memory");
}
__device__ __forceinline__ uint4 ld_msg(const uint4* p) {
    uint4 v;
    asm volatile("{\n.reg .b128 t;\n.reg .b64 lo, hi;\nld.relaxed.gpu.global.b128 t, [%4];\nmov.b128 {lo,hi}, t;\n"
                 "mov.b64 {%0,%1}, lo;\nmov.b64 {%2,%3}, hi;\n}"
                 : "=r"(v.x), "=r"(v.y), "=r"(v.z), "=r"(v.w) : "l"(p) : "memory");
    return v;
}
template <int N>
__device__ __forceinline__ float2 gather_msgs(const uint4* p, int stride, uint32_t tag) {
    uint4 v[N];
#pragma unroll
    for (int i = 0; i < N; i++) v[i] = ld_msg(p + i * stride);
    for (int n = 0;; n++) {
        bool ok = true;
#pragma unroll
        for (int i = 0; i < N; i++) ok = ok && (v[i].w == tag);
        if (__all_sync(0xffffffffu, ok)) break;
        if (POLL_SLEEP > 0) __nanosleep(POLL_SLEEP);
#pragma unroll
        for (int i = 0; i < N; i++) if (v[i].w != tag) v[i] = ld_msg(p + i * stride);
        if (n > (1 << 21)) __trap();
    }
    float a = __uint_as_float(v[0].x), b = __uint_as_float(v[0].y);
#pragma unroll
    for (int i = 1; i < N; i++) { a += __uint_as_float(v[i].x); b += __uint_as_float(v[i].y); }
    a += __shfl_xor_sync(0xffffffffu, a, 8);
    b += __shfl_xor_sync(0xffffffffu, b, 8);
    a += __shfl_xor_sync(0xffffffffu, a, 16);
    b += __shfl_xor_sync(0xffffffffu, b, 16);
    return make_float2(a, b);
}
__device__ __forceinline__ void gather_msgs2(const uint4* p, const uint4* q, uint32_t tag, float2& u, float2& w, uint32_t sm) {
    uint4 v[4];
    v[0] = ld_msg(p); v[1] = ld_msg(p + 32); v[2] = ld_msg(q); v[3] = ld_msg(q + 32);
    for (int n = 0;; n++) {
        const bool ok = v[0].w == tag && v[1].w == tag && v[2].w == tag && v[3].w == tag;
        if (__all_sync(0xffffffffu, ok)) break;
        if (POLL_SLEEP > 0) __nanosleep(POLL_SLEEP);
        if (v[0].w != tag) v[0] = ld_msg(p);
        if (v[1].w != tag) v[1] = ld_msg(p + 32);
        if (v[2].w != tag) v[2] = ld_msg(q);
        if (v[3].w != tag) v[3] = ld_msg(q + 32);
        if (n > (1 << 21)) __trap();
    }
    float a = __uint_as_float(v[0].x) + __uint_as_float(v[1].x), b = __uint_as_float(v[0].y) + __uint_as_float(v[1].y);
    float c = __uint_as_float(v[2].x) + __uint_as_float(v[3].x), d = __uint_as_float(v[2].y) + __uint_as_float(v[3].y);
#pragma unroll
    for (int o = 8; o <= 16; o <<= 1) {
        a += __shfl_xor_sync(0xffffffffu, a, o); b += __shfl_xor_sync(0xffffffffu, b, o);
        c += __shfl_xor_sync(0xffffffffu, c, o); d += __shfl_xor_sync(0xffffffffu, d, o);
    }
    u = make_float2(a, b);
    w = make_float2(c, d);
}
__device__ __forceinline__ void ldsm4(uint32_t (&a)[4], uint32_t addr) {
    asm volatile("ldmatrix.sync.aligned.m8n8.x4.shared.b16 {%0,%1,%2,%3}, [%4];"
                 : "=r"(a[0]), "=r"(a[1]), "=r"(a[2]), "=r"(a[3]) : "r"(addr) : "memory");
}
__device__ __forceinline__ void ldsm4t(uint32_t (&a)[4], uint32_t addr) {
    asm volatile("ldmatrix.sync.aligned.m8n8.x4.trans.shared.b16 {%0,%1,%2,%3}, [%4];"
                 : "=r"(a[0]), "=r"(a[1]), "=r"(a[2]), "=r"(a[3]) : "r"(addr) : "memory");
}
__device__ __forceinline__ void ldsm2t(uint32_t (&a)[2], uint32_t addr) {
    asm volatile("ldmatrix.sync.aligned.m8n8.x2.trans.shared.b16 {%0,%1}, [%2];"
                 : "=r"(a[0]), "=r"(a[1]) : "r"(addr) : "memory");
}
__device__ __forceinline__ void mma16(float (&c)[4], const uint32_t (&a)[4], uint32_t b0, uint32_t b1) {
    asm volatile("mma.sync.aligned.m16n8k16.row.col.f32.bf16.bf16.f32 {%0,%1,%2,%3}, {%4,%5,%6,%7}, {%8,%9}, {%0,%1,%2,%3};"
                 : "+f"(c[0]), "+f"(c[1]), "+f"(c[2]), "+f"(c[3])
                 : "r"(a[0]), "r"(a[1]), "r"(a[2]), "r"(a[3]), "r"(b0), "r"(b1));
}
__device__ __forceinline__ void mma8(float (&c)[4], const uint32_t (&a)[2], uint32_t b0) {
    asm volatile("mma.sync.aligned.m16n8k8.row.col.f32.bf16.bf16.f32 {%0,%1,%2,%3}, {%4,%5}, {%6}, {%0,%1,%2,%3};"
                 : "+f"(c[0]), "+f"(c[1]), "+f"(c[2]), "+f"(c[3]) : "r"(a[0]), "r"(a[1]), "r"(b0));
}
__device__ __forceinline__ uint32_t lds32(uint32_t a) { uint32_t v; asm volatile("ld.shared.b32 %0, [%1];" : "=r"(v) : "r"(a) : "memory"); return v; }
__device__ __forceinline__ float ldsf(uint32_t a) { float v; asm volatile("ld.shared.f32 %0, [%1];" : "=f"(v) : "r"(a) : "memory"); return v; }
__device__ __forceinline__ float2 ldsf2(uint32_t a) { float2 v; asm volatile("ld.shared.v2.f32 {%0,%1}, [%2];" : "=f"(v.x), "=f"(v.y) : "r"(a) : "memory"); return v; }
__device__ __forceinline__ float4 ldsf4(uint32_t a) { float4 v; asm volatile("ld.shared.v4.f32 {%0,%1,%2,%3}, [%4];" : "=f"(v.x), "=f"(v.y), "=f"(v.z), "=f"(v.w) : "r"(a) : "memory"); return v; }
__device__ __forceinline__ uint4 lds128(uint32_t a) { uint4 v; asm volatile("ld.shared.v4.b32 {%0,%1,%2,%3}, [%4];" : "=r"(v.x), "=r"(v.y), "=r"(v.z), "=r"(v.w) : "r"(a) : "memory"); return v; }
__device__ __forceinline__ void sts128(uint32_t a, uint32_t x, uint32_t y, uint32_t z, uint32_t w) { asm volatile("st.shared.v4.b32 [%0], {%1,%2,%3,%4};" ::"r"(a), "r"(x), "r"(y), "r"(z), "r"(w) : "memory"); }
__device__ __forceinline__ void stsf(uint32_t a, float v) { asm volatile("st.shared.f32 [%0], %1;" ::"r"(a), "f"(v) : "memory"); }
__device__ __forceinline__ void stsf2(uint32_t a, float x, float y) { asm volatile("st.shared.v2.f32 [%0], {%1,%2};" ::"r"(a), "f"(x), "f"(y) : "memory"); }
__device__ __forceinline__ void sts32(uint32_t a, uint32_t v) { asm volatile("st.shared.b32 [%0], %1;" ::"r"(a), "r"(v) : "memory"); }
__device__ __forceinline__ void sts_bf16(uint32_t a, float v) {
    asm volatile("st.shared.b16 [%0], %1;" ::"r"(a), "h"(__bfloat16_as_ushort(__float2bfloat16_rn(v))) : "memory");
}
__device__ __forceinline__ float bf16r(float x) { return __bfloat162float(__float2bfloat16_rn(x)); }
__device__ __forceinline__ float silu_bf16(float x) { return bf16r(__fdividef(x, 1.0f + __expf(-x))); }

template <int PITCH>
__device__ __forceinline__ uint32_t gemv_addr(uint32_t tile, int col0, int lane) {
    return tile + ((lane & 7) + 8 * (lane >> 4)) * PITCH + (col0 + 8 * ((lane >> 3) & 1)) * 2;
}
template <int PITCH, int NK>
__device__ __forceinline__ void gemv_tile(float (&acc0)[4], float (&acc1)[4], uint32_t a_addr, uint32_t v_addr) {
#pragma unroll
    for (int ks = 0; ks < NK; ks++) {
        uint32_t a[4];
        ldsm4t(a, a_addr + ks * 16 * PITCH);
        const uint32_t b0 = lds32(v_addr + ks * 32), b1 = lds32(v_addr + ks * 32 + 16);
        if (ks & 1) mma16(acc1, a, b0, b1); else mma16(acc0, a, b0, b1);
    }
}

__device__ __forceinline__ float2 ln_stats(const float (&x)[18], float shift) {
    float s1 = 0.f, s2 = 0.f;
#pragma unroll
    for (int i = 0; i < 18; i++) { const float d = x[i] - shift; s1 += d; s2 = fmaf(d, d, s2); }
#pragma unroll
    for (int o = 16; o; o >>= 1) { s1 += __shfl_xor_sync(0xffffffffu, s1, o); s2 += __shfl_xor_sync(0xffffffffu, s2, o); }
    const float md = s1 * (1.0f / D);
    const float var = fmaxf(s2 * (1.0f / D) - md * md, 0.f);
    const float mean = bf16r(shift + md);
    const float den = bf16r(sqrtf(bf16r(bf16r(var) + 1e-5f)));
    return make_float2(mean, __frcp_rn(den));
}
__device__ __forceinline__ float ln_norm(float x, float2 st) { return bf16r(bf16r(x - st.x) * st.y); }
__device__ __forceinline__ float modulate(float xn, float g1p, float shift) { return bf16r(bf16r(xn * g1p) + shift); }

template <int LO, int HI>
__device__ __forceinline__ void init_barriers(uint32_t bars) {
#pragma unroll
    for (int i = LO; i < HI; i++)
        mbar_init(bars + i * 8, i < B_EMPTY ? 1 : i < B_EMPTY + MAXT ? 4 : i < B_AFREE ? 8 : i == B_AFREE ? 8 : i == B_MODFREE ? 10 : i == B_GATES ? 2 : 1);
}

struct Maps { CUtensorMap mod, wq, k, v, wo, w1, w2; };
struct Ptrs { const void *wq, *v, *wo, *w1, *w2; };

__global__ void __launch_bounds__(NTHREADS, 1)
adaln_decode_kernel(const __grid_constant__ Maps maps, const __grid_constant__ Ptrs ptrs, const __nv_bfloat16* __restrict__ kbase,
                    const __nv_bfloat16* __restrict__ gmod,
                    const __nv_bfloat16* __restrict__ gx,
                    const __nv_bfloat16* __restrict__ gc, __nv_bfloat16* __restrict__ gout) {
    extern __shared__ __align__(1024) unsigned char smem_raw[];
    const uint32_t sm = (uint32_t)__cvta_generic_to_shared(smem_raw);
    const uint32_t bars = sm + O_BAR;
    const int tid = threadIdx.x, warp = tid >> 5, lane = tid & 31;
    uint32_t j;
    asm("mov.u32 %0, %%cluster_ctarank;" : "=r"(j));
    const int h = blockIdx.x / CS;
    const int nt = j < 4 ? 11 : 10;
    const int tile0 = j < 4 ? 11 * j : 44 + 10 * (j - 4);
#define BAR(i) (bars + (i) * 8)

    if (warp == NCW) {
        uint64_t pol;
        asm volatile("createpolicy.fractional.L2::evict_first.b64 %0, 1.0;" : "=l"(pol));
        if (lane == 0) PROF1(0);
        const uint32_t tstart = __shfl_sync(0xffffffffu, gtime32(), 0);
        if (lane == 0) {
            init_barriers<B_MODA, B_K>(bars);
            asm volatile("fence.mbarrier_init.release.cluster;" ::: "memory");
            mbar_expect_tx(BAR(B_MODA), SZ_MOD);
            tma2d(sm + O_MODA, &maps.mod, (h & 1) * D + 96 * j, (h >> 1) * 72, BAR(B_MODA), pol);
#pragma unroll
            for (int i = 0; i < NFIRST; i++) {
                mbar_expect_tx(BAR(B_WQ + i), SZ_WQ);
                tma3d(sm + O_WQ + i * SZ_WQ, &maps.wq, 0, 96 * j + i * 32, h * 4, BAR(B_WQ + i), pol);
            }
            PROF1(18);
        }
        __syncwarp();
        bar_arrive(0, NCT + 32);
        asm volatile("barrier.cluster.arrive.relaxed.aligned;" ::: "memory");
        bar_sync(3, 128 + MONW);
        if (lane != 0) return;
        uint32_t qm = 0, q0 = NFIRST > 2 ? BAR(B_WQ + NFIRST - 4) : 0, q1 = NFIRST > 1 ? BAR(B_WQ + NFIRST - 3) : 0,
                 q2 = NFIRST > 0 ? BAR(B_WQ + NFIRST - 2) : 0, q3 = BAR(B_WQ + NFIRST - 1);
#define MON() do {} while (0)
#define PACE(bytes_all, rate) { while ((int)(gtime32() - due) < 0) {} due += (uint32_t)((bytes_all) / (rate)); }
#define STAGE_BEGIN(depth, bar_, bytes_all, rate) \
        { const uint32_t w_ = (depth) == 5 ? qm : (depth) == 4 ? q0 : (depth) == 3 ? q1 : q2; if (w_) PWAIT(w_); qm = q0; q0 = q1; q1 = q2; q2 = q3; q3 = (bar_); PACE(bytes_all, rate); }
        const int cb = h * CS + j;
        uint32_t due = tstart - PACE_LEAD + (D * 2 * D * 2 + NFIRST * (D * 4096 * 2 / 3)) / PACE_A;
#pragma unroll 1
        for (int i = NFIRST; i < 3; i++) {
            const uint32_t b = BAR(B_WQ + i);
            STAGE_BEGIN(DEPTH_A, b, D * 4096 * 2 / 3, PACE_A);
            mbar_expect_tx(b, SZ_WQ);
            tma3d(sm + O_WQ + i * SZ_WQ, &maps.wq, 0, 96 * j + i * 32, h * 4, b, pol);
            MON();
        }
#pragma unroll 1
        for (int i = 0; i < 2; i++) {
            const uint32_t b = BAR(B_MODB + i);
            STAGE_BEGIN(DEPTH_A, b, D * 4 * D * 2 / 2, PACE_A);
            mbar_expect_tx(b, SZ_MOD);
            tma2d(sm + O_MODB + i * SZ_MOD, &maps.mod, (2 + (h & 3)) * D + 96 * j, (h >> 2) * 144 + i * 72, b, pol);
            MON();
        }
        {
            const int row0 = h * SK + (SK - WINDOW) + tile0 * 64;
            int slot = 0;
#pragma unroll 1
            for (int n = 0; n < 2 * nt; n++) {
                const bool isv = n >= nt;
                const int t = isv ? n - nt : n;
                const uint32_t b = BAR((isv ? B_V : B_K) + t), dst = sm + slot_off(slot);
                const CUtensorMap* m = isv ? &maps.v : &maps.k;
                STAGE_BEGIN(DEPTH_KV, b, (nt == 11 ? NKV * WINDOW * DH * 4 / 22 : NKV * WINDOW * DH * 4 / 20), PACE_GBPS);
                if (n == NRING) PWAIT(BAR(B_MODFREE));
                if (n >= NSLOT) { const int pn = n - NSLOT; PWAIT(BAR(B_EMPTY + (pn < nt ? pn : MAXT + pn - nt))); }
                mbar_expect_tx(b, SZ_KV);
                tma2d(dst, m, 0, row0 + t * 64, b, pol);
                tma2d(dst + 8192, m, 64, row0 + t * 64, b, pol);
                MON();
                slot = slot == NSLOT - 1 ? 0 : slot + 1;
                if (n == 0) PROF1(22);
                if (n == nt) PROF1(1);
            }
        }
#pragma unroll 1
        for (int i = 0; i < 4; i++) {
            const uint32_t b = BAR(B_WO + i);
            STAGE_BEGIN(DEPTH_WO, b, D * 4096 * 2 / 4, PACE_WO);
            if (i == 0) { PWAIT(BAR(B_AFREE)); PWAIT(BAR(B_MODFREE)); PROF1(2); }
            mbar_expect_tx(b, SZ_WO);
            tma2d(sm + O_WO + i * SZ_WO, &maps.wo, 96 * j, h * 256 + i * 64, b, pol);
            MON();
        }
        auto issue_w2 = [&](int i, bool early) {
            const uint32_t b = BAR(B_W2 + i);
            if (early) { STAGE_BEGIN(DEPTH_W2, b, D * FF * 2 / 3, PACE_W2E); } else { STAGE_BEGIN(DEPTH_W2, b, D * FF * 2 / 3, PACE_W2); }
            if (early && i == 0) PWAIT(BAR(B_EMPTY + MAXT + nt - 1));
            mbar_expect_tx(b, SZ_W2);
            tma3d(sm + O_W2 + i * SZ_W2, &maps.w2, 0, 0, cb * 48 + i * 16, b, pol);
            MON();
        };
#pragma unroll 1
        for (int i = 0; i < W2_EARLY; i++) issue_w2(i, true);
#pragma unroll 1
        for (int i = 0; i < 4; i++) {
            const uint32_t b = BAR(B_W1 + i);
            STAGE_BEGIN(DEPTH_W1, b, D * FF * 2 / 4, PACE_W1);
            if (i == 0) {
                PWAIT(BAR(B_EMPTY + MAXT + 14 - nt));
                PWAIT(BAR(B_EMPTY + MAXT + 15 - nt));
            }
            if (i == 2) PWAIT(BAR(B_EMPTY + MAXT + nt - 1));
            mbar_expect_tx(b, SZ_W1);
            tma2d(sm + (i < 2 ? O_W1A + i * SZ_W1 : O_W1B + (i - 2) * SZ_W1), &maps.w1, cb * 48, i * 144, b, pol);
            MON();
        }
#pragma unroll 1
        for (int i = W2_EARLY; i < 3; i++) issue_w2(i, false);
        PROF1(3);
#undef STAGE_BEGIN
#undef MON
        asm volatile("barrier.cluster.wait;" ::: "memory");
        return;
    }

    const int g = lane >> 2, t4 = lane & 3;
    const int r7 = lane & 7, lg = lane >> 3;
    uint4* const a1_out = g_scr.a1 + ((((h & 1) * 6 + j) * 6) * 8 + (h >> 1)) * 8;
    uint4* const a2_out = g_scr.a2 + ((((h & 3) * 6 + j) * 6) * 4 + (h >> 2)) * 8;
    uint4* const c1_out = g_scr.c1 + ((j * 6) * 16 + h) * 8;
    uint4* const d1_out = g_scr.d1 + ((j * 6) * 16 + h) * 8;

    uint32_t xv = 0, cv = 0;
    if (warp >= 9) {
        if (lane == 0) {
            if (warp == 9) init_barriers<B_K, B_EMPTY>(bars);
            else if (warp == 10) init_barriers<B_EMPTY, B_AFREE>(bars);
            else {
                init_barriers<B_AFREE, NBAR>(bars);
                mbar_expect_tx(BAR(B_XQ), CS * 1024);
                mbar_expect_tx(BAR(B_XB), CS * 1040);
                mbar_expect_tx(BAR(B_XC), CS * 384);
                mbar_expect_tx(BAR(B_XG), CS * 768);
                mbar_expect_tx(BAR(B_XD), CS * 384);
            }
            asm volatile("fence.mbarrier_init.release.cluster;" ::: "memory");
        }
        __syncwarp();
        bar_arrive(3, 128 + MONW);
    } else {
        xv = __ldg(reinterpret_cast<const uint32_t*>(gx) + tid);
        cv = __ldg(reinterpret_cast<const uint32_t*>(gc) + tid);
    }
    uint32_t xall[9];
    uint32_t xc0 = 0, xc1 = 0;
    if (warp < 6) {
#pragma unroll
        for (int i = 0; i < 9; i++) xall[i] = __ldg(reinterpret_cast<const uint32_t*>(gx) + lane + 32 * i);
        xc0 = __ldg(reinterpret_cast<const unsigned short*>(gx) + 96 * j + warp * 16 + r7);
        xc1 = __ldg(reinterpret_cast<const unsigned short*>(gx) + 96 * j + warp * 16 + r7 + 8);
    }
    asm volatile("barrier.cluster.arrive.relaxed.aligned;" ::: "memory");
    uint32_t epoch = 0;
    if (tid == 288) epoch = *(volatile unsigned*)&g_scr.epoch;
    if (t4 == 0) {
        if (warp < 6) st_msg(a1_out + warp * 64 + g, 0.f, 0.f, 0);
        else if (warp >= 8) {
            st_msg(a2_out + (warp - 8) * 32 + g, 0.f, 0.f, 0);
            if (warp < 10) st_msg(a2_out + (warp - 4) * 32 + g, 0.f, 0.f, 0);
        }
    }
    if (tid < 288) {
        stsf2(sm + O_XS + tid * 8, __uint_as_float(xv << 16), __uint_as_float(xv & 0xffff0000u));
        const float c0 = silu_bf16(__uint_as_float(cv << 16)), c1 = silu_bf16(__uint_as_float(cv & 0xffff0000u));
        sts32(sm + O_SC + tid * 4, (__float_as_uint(c0) >> 16) | (__float_as_uint(c1) & 0xffff0000u));
    }
    if (tid == 288) sts32(sm + O_TAG, epoch + 1);
    float xn0 = 0.f, xn1 = 0.f;
    if (warp < 6) {
        float xr[18];
#pragma unroll
        for (int i = 0; i < 9; i++) { xr[2 * i] = __uint_as_float(xall[i] << 16); xr[2 * i + 1] = __uint_as_float(xall[i] & 0xffff0000u); }
        const float2 st = ln_stats(xr, __shfl_sync(0xffffffffu, xr[0], 0));
        xn0 = ln_norm(__uint_as_float(xc0 << 16), st);
        xn1 = ln_norm(__uint_as_float(xc1 << 16), st);
    }
    if (warp == 0) PROF(21);
    bar_sync(0, NCT + 32);
    const uint32_t tag = lds32(sm + O_TAG);
    if (tid == 6 * 32) {
        asm volatile("prefetch.tensormap [%0];" ::"l"(&maps.k) : "memory");
        asm volatile("prefetch.tensormap [%0];" ::"l"(&maps.v) : "memory");
    }
    if (tid == 7 * 32) {
        asm volatile("prefetch.tensormap [%0];" ::"l"(&maps.wo) : "memory");
        asm volatile("prefetch.tensormap [%0];" ::"l"(&maps.w1) : "memory");
        asm volatile("prefetch.tensormap [%0];" ::"l"(&maps.w2) : "memory");
    }
    if (warp == 0) PROF(4);

    if (warp < 6) {
        float acc0[4] = {0.f, 0.f, 0.f, 0.f}, acc1[4] = {0.f, 0.f, 0.f, 0.f};
        const uint32_t va = sm + O_SC + ((h >> 1) * 72 + 2 * t4) * 2;
        mbar_wait(BAR(B_MODA));
        if (warp == 0) PROF(19);
        gemv_tile<P_MOD, 4>(acc0, acc1, gemv_addr<P_MOD>(sm + O_MODA, warp * 16, lane), va);
        {
            uint32_t a[2];
            ldsm2t(a, sm + O_MODA + (64 + r7) * P_MOD + (warp * 16 + 8 * (lg & 1)) * 2);
            mma8(acc0, a, lds32(va + 128));
        }
        if (t4 == 0) st_msg(a1_out + warp * 64 + g, acc0[0] + acc1[0], acc0[2] + acc1[2], tag);
        if (lane == 0) mbar_arrive(BAR(B_MODFREE));
        if (warp == 0) PROF(5);
        const uint4* in = g_scr.a1 + (j * 6 + warp) * 64 + lane;
        float2 sa, ca;
        gather_msgs2(in, in + 36 * 64, tag, sa, ca, sm);
        if (lg == 0) {
            const int c = warp * 16 + r7;
            sts_bf16(sm + O_HV + c * 2, modulate(xn0, bf16r(1.f + bf16r(ca.x)), bf16r(sa.x)));
            sts_bf16(sm + O_HV + (c + 8) * 2, modulate(xn1, bf16r(1.f + bf16r(ca.y)), bf16r(sa.y)));
        }
        if (warp == 0) PROF(6);
    }
    asm volatile("barrier.cluster.wait.aligned;" ::: "memory");

    if (warp < 8) {
        bar_sync(1, 256);
        float a00[4] = {0.f, 0.f, 0.f, 0.f}, a01[4] = {0.f, 0.f, 0.f, 0.f};
        float a10[4] = {0.f, 0.f, 0.f, 0.f}, a11[4] = {0.f, 0.f, 0.f, 0.f};
        const uint32_t va = sm + O_HV + 4 * t4;
        const uint32_t a_off = (warp >> 1) * 4096 + (r7 + 8 * (lg >> 1)) * 128 + (((4 * (warp & 1) + (lg & 1)) ^ r7) << 4);
#pragma unroll
        for (int i = 0; i < 3; i++) {
            mbar_wait(BAR(B_WQ + i));
            if (i == 2 && warp == 4) PROF(20);
#pragma unroll
            for (int k2 = 0; k2 < 2; k2++) {
                const int ks = 2 * i + k2;
                const uint32_t b0 = lds32(va + ks * 32), b1 = lds32(va + ks * 32 + 16);
                uint32_t a[4];
                ldsm4t(a, sm + O_WQ + i * SZ_WQ + k2 * 2048 + a_off);
                if (k2) mma16(a01, a, b0, b1); else mma16(a00, a, b0, b1);
                ldsm4t(a, sm + O_WQ + i * SZ_WQ + k2 * 2048 + (a_off ^ 32));
                if (k2) mma16(a11, a, b0, b1); else mma16(a10, a, b0, b1);
            }
        }
        const uint32_t dst = sm + O_QBUF + j * 1024 + (warp * 8 + g) * 16;
        const float v0 = a00[0] + a01[0], v1 = a00[2] + a01[2], v2 = a10[0] + a11[0], v3 = a10[2] + a11[2];
        st_async4(mapa(dst, t4), v0, v1, v2, v3, mapa(BAR(B_XQ), t4));
        if (t4 < 2) st_async4(mapa(dst, t4 + 4), v0, v1, v2, v3, mapa(BAR(B_XQ), t4 + 4));
        if (lane == 0) mbar_arrive(BAR(B_AFREE));
        mbar_wait_cluster(BAR(B_XQ));
        float q = 0.f;
#pragma unroll
        for (int s = 0; s < CS; s++) q += ldsf(sm + O_QBUF + s * 1024 + tid * 4);
        const int e = tid & 3;
        const int n = warp * 32 + (e >> 1) * 16 + g + 8 * (e & 1);
        sts_bf16(sm + O_QV + n * 2, q);
    }
    if (warp >= 8) {
        mbar_wait(BAR(B_MODB));
        mbar_wait(BAR(B_MODB + 1));
        const uint32_t va = sm + O_SC + ((h >> 2) * 144 + 2 * t4) * 2;
        for (int l = warp - 8; l < 6; l += 4) {
            float acc0[4] = {0.f, 0.f, 0.f, 0.f}, acc1[4] = {0.f, 0.f, 0.f, 0.f};
            gemv_tile<P_MOD, 9>(acc0, acc1, gemv_addr<P_MOD>(sm + O_MODB, l * 16, lane), va);
            if (t4 == 0) st_msg(a2_out + l * 32 + g, acc0[0] + acc1[0], acc0[2] + acc1[2], tag);
        }
        __syncwarp();
        if (lane == 0) mbar_arrive(BAR(B_MODFREE));
    }

    bar_sync(2, NCT);
    if (warp == 0) PROF(7);
    uint32_t qb[16];
#pragma unroll
    for (int ks = 0; ks < 8; ks++) {
        const uint32_t a = sm + O_QV + ((g & 1) * 128 + ks * 16 + 2 * t4) * 2;
        qb[2 * ks] = lds32(a);
        qb[2 * ks + 1] = lds32(a + 16);
    }

    float sc[4];
    {
        const int grp = warp >> 2, mi = lg;
        const uint32_t a_off = (16 * (warp & 3) + r7 + 8 * (mi & 1)) * 128 + (((mi >> 1) ^ r7) << 4);
        float mx = -INFINITY;
#pragma unroll
        for (int it = 0; it < 4; it++) {
            const int t = grp + 3 * it;
            sc[it] = -INFINITY;
            if (t < nt) {
                mbar_wait(BAR(B_K + t));
                const uint32_t base = sm + slot_off(t % NSLOT);
                float c0[4] = {0.f, 0.f, 0.f, 0.f}, c1[4] = {0.f, 0.f, 0.f, 0.f};
#pragma unroll
                for (int ks = 0; ks < 8; ks++) {
                    uint32_t a[4];
                    ldsm4(a, base + (ks >> 2) * 8192 + (a_off ^ ((ks & 3) << 5)));
                    if (ks & 1) mma16(c1, a, qb[2 * ks], qb[2 * ks + 1]); else mma16(c0, a, qb[2 * ks], qb[2 * ks + 1]);
                }
                __syncwarp();
                if (lane == 0) mbar_arrive(BAR(B_EMPTY + t));
                const float v = t4 == 0 ? c0[0] + c1[0] : t4 == 1 ? c0[1] + c1[1] : t4 == 2 ? c0[2] + c1[2] : c0[3] + c1[3];
                sc[it] = bf16r(bf16r(v) * 0.08838834764831845f);
                mx = fmaxf(mx, sc[it]);
            }
        }
        mx = fmaxf(mx, __shfl_xor_sync(0xffffffffu, mx, 2));
        mx = fmaxf(mx, __shfl_xor_sync(0xffffffffu, mx, 4));
        mx = fmaxf(mx, __shfl_xor_sync(0xffffffffu, mx, 8));
        mx = fmaxf(mx, __shfl_xor_sync(0xffffffffu, mx, 16));
        if (lane < 2) stsf(sm + O_WMAX + (warp * 2 + lane) * 4, mx);
    }
    bar_sync(2, NCT);
    if (warp == 0) PROF(8);
    float cta_max;
    {
        const int hd = t4 & 1, grp = warp >> 2;
        float m = -INFINITY;
#pragma unroll
        for (int w = 0; w < NCW; w++) m = fmaxf(m, ldsf(sm + O_WMAX + (w * 2 + hd) * 4));
        cta_max = m;
        float l = 0.f;
#pragma unroll
        for (int it = 0; it < 4; it++) {
            const int t = grp + 3 * it;
            if (t < nt) {
                const float p = __expf(sc[it] - m);
                l += p;
                sts_bf16(sm + O_PV + (hd * PV_PITCH + t * 64 + 16 * (warp & 3) + g + 8 * (t4 >> 1)) * 2, p);
            }
        }
        l += __shfl_xor_sync(0xffffffffu, l, 2);
        l += __shfl_xor_sync(0xffffffffu, l, 4);
        l += __shfl_xor_sync(0xffffffffu, l, 8);
        l += __shfl_xor_sync(0xffffffffu, l, 16);
        if (lane < 2) stsf(sm + O_WL + (warp * 2 + lane) * 4, l);
    }
    if (warp < 6 && t4 == 0) {
        st_msg(c1_out + warp * 128 + g, 0.f, 0.f, 0);
        st_msg(d1_out + warp * 128 + g, 0.f, 0.f, 0);
    }
    bar_sync(2, NCT);

    if (warp >= 8) {
        const int m = warp - 8;
#pragma unroll 1
        for (int l = 0; l < 6; l++) {
            const float2 v = gather_msgs<1>(g_scr.a2 + ((m * 6 + j) * 6 + l) * 32 + lane, 0, tag);
            float a = bf16r(v.x), b = bf16r(v.y);
            if (m == 0 || m == 3) {
                if (lg == 0) stsf2(sm + (m == 0 ? O_GA : O_GB) + (l * 8 + r7) * 8, a, b);
            } else {
                if (m == 2) { a = bf16r(1.f + a); b = bf16r(1.f + b); }
                const uint32_t dst = sm + (m == 1 ? O_SB : O_G1P) + ((j * 6 + l) * 8 + r7) * 8;
                st_async2(mapa(dst, lg), a, b, mapa(BAR(B_XG), lg));
                if (lg < 2) st_async2(mapa(dst, lg + 4), a, b, mapa(BAR(B_XG), lg + 4));
            }
        }
        __syncwarp();
        if (lane == 0 && (m == 0 || m == 3)) mbar_arrive(BAR(B_GATES));
        if (warp == 8) {
            const float m0 = __shfl_sync(0xffffffffu, cta_max, 0), m1 = __shfl_sync(0xffffffffu, cta_max, 1);
            float l0 = 0.f, l1 = 0.f;
#pragma unroll
            for (int w = 0; w < NCW; w++) { const float2 v = ldsf2(sm + O_WL + w * 8); l0 += v.x; l1 += v.y; }
            if (lane < CS) st_async4(mapa(sm + O_MLBUF + j * 16, lane), m0, m1, l0, l1, mapa(BAR(B_XB), lane));
        }
    } else {
        const int mi = lg;
        const uint32_t a_off = (warp >> 2) * 8192 + (r7 + 8 * (mi >> 1)) * 128 + (((2 * (warp & 3) + (mi & 1)) ^ r7) << 4);
        const uint32_t pa = sm + O_PV + ((g & 1) * PV_PITCH + 2 * t4) * 2;
        float c0[4] = {0.f, 0.f, 0.f, 0.f}, c1[4] = {0.f, 0.f, 0.f, 0.f};
#pragma unroll 1
        for (int t = 0; t < nt; t++) {
            uint32_t b[8];
#pragma unroll
            for (int ks = 0; ks < 4; ks++) { b[2 * ks] = lds32(pa + (t * 64 + ks * 16) * 2); b[2 * ks + 1] = lds32(pa + (t * 64 + ks * 16) * 2 + 16); }
            mbar_wait(BAR(B_V + t));
            const uint32_t base = sm + slot_off((nt + t) % NSLOT) + a_off;
#pragma unroll
            for (int ks = 0; ks < 4; ks++) {
                uint32_t a[4];
                ldsm4t(a, base + ks * 2048);
                if (ks & 1) mma16(c1, a, b[2 * ks], b[2 * ks + 1]); else mma16(c0, a, b[2 * ks], b[2 * ks + 1]);
            }
            __syncwarp();
            if (lane == 0) mbar_arrive(BAR(B_EMPTY + MAXT + t));
        }
        if (warp == 0) PROF(9);
        const uint32_t dst = sm + O_OBUF + j * 1024 + (warp * 8 + g) * 16;
        const float v0 = c0[0] + c1[0], v1 = c0[1] + c1[1], v2 = c0[2] + c1[2], v3 = c0[3] + c1[3];
        st_async4(mapa(dst, t4), v0, v1, v2, v3, mapa(BAR(B_XB), t4));
        if (t4 < 2) st_async4(mapa(dst, t4 + 4), v0, v1, v2, v3, mapa(BAR(B_XB), t4 + 4));
        mbar_wait_cluster(BAR(B_XB));
        {
            const int e = tid & 3, hd = e & 1;
            float ms[CS], ls[CS], M = -INFINITY;
#pragma unroll
            for (int s = 0; s < CS; s++) {
                const float4 v = ldsf4(sm + O_MLBUF + s * 16);
                ms[s] = hd ? v.y : v.x; ls[s] = hd ? v.w : v.z;
                M = fmaxf(M, ms[s]);
            }
            float L = 0.f, o = 0.f;
#pragma unroll
            for (int s = 0; s < CS; s++) {
                const float w = __expf(ms[s] - M);
                L = fmaf(w, ls[s], L);
                o = fmaf(w, ldsf(sm + O_OBUF + s * 1024 + tid * 4), o);
            }
            const int n = hd * 128 + warp * 16 + g + 8 * (e >> 1);
            sts_bf16(sm + O_OV + n * 2, o / L);
        }
        bar_sync(1, 256);
        if (warp == 0) PROF(10);
        if (warp < 6) {
            float acc0[4] = {0.f, 0.f, 0.f, 0.f}, acc1[4] = {0.f, 0.f, 0.f, 0.f};
            const uint32_t va = sm + O_OV + 4 * t4;
#pragma unroll
            for (int i = 0; i < 4; i++) {
                mbar_wait(BAR(B_WO + i));
                gemv_tile<P_WO, 4>(acc0, acc1, gemv_addr<P_WO>(sm + O_WO + i * SZ_WO, warp * 16, lane), va + i * 128);
            }
            if (t4 == 0) st_msg(c1_out + warp * 128 + g, acc0[0] + acc1[0], acc0[2] + acc1[2], tag);
            if (warp == 0) PROF(11);
            const int c = 96 * j + warp * 16 + r7;
            const float x0 = ldsf(sm + O_XS + c * 4), x1 = ldsf(sm + O_XS + (c + 8) * 4);
            mbar_wait(BAR(B_GATES));
            const float2 ga = ldsf2(sm + O_GA + (warp * 8 + r7) * 8);
            const float2 at = gather_msgs<4>(g_scr.c1 + (j * 6 + warp) * 128 + lane, 32, tag);
            const float y0 = bf16r(x0 + bf16r(ga.x * bf16r(at.x))), y1 = bf16r(x1 + bf16r(ga.y * bf16r(at.y)));
            const uint32_t dst2 = sm + O_X2 + ((j * 6 + warp) * 8 + r7) * 8;
            st_async2(mapa(dst2, lg), y0, y1, mapa(BAR(B_XC), lg));
            if (lg < 2) st_async2(mapa(dst2, lg + 4), y0, y1, mapa(BAR(B_XC), lg + 4));
            if (warp == 0) PROF(12);
        }
    }

    mbar_wait_cluster(BAR(B_XG));
    mbar_wait_cluster(BAR(B_XC));
    {
        float xr[18];
#pragma unroll
        for (int i = 0; i < 9; i++) { const float2 v = ldsf2(sm + O_X2 + (lane + 32 * i) * 8); xr[2 * i] = v.x; xr[2 * i + 1] = v.y; }
        const float2 st = ln_stats(xr, ldsf(sm + O_X2));
        if (tid < 288) {
            const float2 x = ldsf2(sm + O_X2 + tid * 8), g1 = ldsf2(sm + O_G1P + tid * 8), sb = ldsf2(sm + O_SB + tid * 8);
            const int c = (tid >> 3) * 16 + (tid & 7);
            sts_bf16(sm + O_H2 + c * 2, modulate(ln_norm(x.x, st), g1.x, sb.x));
            sts_bf16(sm + O_H2 + (c + 8) * 2, modulate(ln_norm(x.y, st), g1.y, sb.y));
        }
    }
    bar_sync(2, NCT);
    if (warp == 0) PROF(13);

    {
        const int mt = warp % 3, kq = warp / 3;
        float acc0[4] = {0.f, 0.f, 0.f, 0.f}, acc1[4] = {0.f, 0.f, 0.f, 0.f};
        const uint32_t tile = sm + (kq < 2 ? O_W1A + kq * SZ_W1 : O_W1B + (kq - 2) * SZ_W1);
        mbar_wait(BAR(B_W1 + kq));
        gemv_tile<P_W1, 9>(acc0, acc1, gemv_addr<P_W1>(tile, mt * 16, lane), sm + O_H2 + (kq * 144 + 2 * t4) * 2);
        if (t4 == 0) {
            stsf(sm + O_RED1 + (kq * 48 + mt * 16 + g) * 4, acc0[0] + acc1[0]);
            stsf(sm + O_RED1 + (kq * 48 + mt * 16 + g + 8) * 4, acc0[2] + acc1[2]);
        }
    }
    bar_sync(2, NCT);
    if (warp == 0) PROF(14);

    {
        const int pi = lane < 24 ? lane : 0;
        float2 s = ldsf2(sm + O_RED1 + pi * 8);
#pragma unroll
        for (int q = 1; q < 4; q++) { const float2 v = ldsf2(sm + O_RED1 + q * 192 + pi * 8); s.x += v.x; s.y += v.y; }
        const float u0 = silu_bf16(bf16r(s.x)), u1 = silu_bf16(bf16r(s.y));
        const uint32_t pk = (__float_as_uint(u0) >> 16) | (__float_as_uint(u1) & 0xffff0000u);
        uint32_t b[6];
#pragma unroll
        for (int ks = 0; ks < 3; ks++) {
            b[2 * ks] = __shfl_sync(0xffffffffu, pk, 8 * ks + t4);
            b[2 * ks + 1] = __shfl_sync(0xffffffffu, pk, 8 * ks + 4 + t4);
        }
        float acc[3][4];
        const uint32_t a_addr = gemv_addr<P_W2>(sm + O_W2 + (warp >> 2) * 400, (warp & 3) * 48, lane);
#pragma unroll
        for (int mt = 0; mt < 3; mt++) acc[mt][0] = acc[mt][1] = acc[mt][2] = acc[mt][3] = 0.f;
#pragma unroll
        for (int ks = 0; ks < 3; ks++) {
            mbar_wait(BAR(B_W2 + ks));
#pragma unroll
            for (int mt = 0; mt < 3; mt++) {
                uint32_t a[4];
                ldsm4t(a, a_addr + ks * SZ_W2 + mt * 32);
                mma16(acc[mt], a, b[2 * ks], b[2 * ks + 1]);
            }
        }
        if (t4 < 3) {
            const float v0 = t4 == 0 ? acc[0][0] : t4 == 1 ? acc[1][0] : acc[2][0];
            const float v1 = t4 == 0 ? acc[0][2] : t4 == 1 ? acc[1][2] : acc[2][2];
            const int dstj = warp >> 1;
            const uint32_t dst = sm + O_D0 + ((j * 6 + (warp & 1) * 3 + t4) * 8 + g) * 8;
            st_async2(mapa(dst, dstj), v0, v1, mapa(BAR(B_XD), dstj));
        }
    }
    if (warp == 0) PROF(15);

    if (warp < 6) {
        mbar_wait_cluster(BAR(B_XD));
        if (t4 == 0) {
            float2 s = ldsf2(sm + O_D0 + (warp * 8 + g) * 8);
#pragma unroll
            for (int q = 1; q < CS; q++) { const float2 v = ldsf2(sm + O_D0 + ((q * 6 + warp) * 8 + g) * 8); s.x += v.x; s.y += v.y; }
            st_msg(d1_out + warp * 128 + g, s.x, s.y, tag);
        }
        if (warp == 0) PROF(16);
        if (warp == h) {
            const float2 x2 = ldsf2(sm + O_X2 + ((j * 6 + warp) * 8 + r7) * 8);
            const float2 gb = ldsf2(sm + O_GB + (warp * 8 + r7) * 8);
            const float2 y = gather_msgs<4>(g_scr.d1 + (j * 6 + warp) * 128 + lane, 32, tag);
            if (lg == 0) {
                const int c = 96 * j + warp * 16 + r7;
                gout[c] = __float2bfloat16_rn(x2.x + bf16r(gb.x * bf16r(y.x)));
                gout[c + 8] = __float2bfloat16_rn(x2.y + bf16r(gb.y * bf16r(y.y)));
            }
            if (blockIdx.x == 0 && lane == 0) *(volatile unsigned*)&g_scr.epoch = tag;
            PROF(17);
        }
    }
#undef BAR
}

typedef CUresult (*EncodeTiledFn)(CUtensorMap*, CUtensorMapDataType, cuuint32_t, void*, const cuuint64_t*,
                                  const cuuint64_t*, const cuuint32_t*, const cuuint32_t*, CUtensorMapInterleave,
                                  CUtensorMapSwizzle, CUtensorMapL2promotion, CUtensorMapFloatOOBfill);

void encode2d(EncodeTiledFn enc, CUtensorMap* m, const void* base, uint64_t rows, uint64_t cols, uint32_t box_cols,
              uint32_t box_rows, CUtensorMapSwizzle swz, int promo = 0) {
    cuuint64_t dims[2] = {cols, rows};
    cuuint64_t strides[1] = {cols * 2};
    cuuint32_t box[2] = {box_cols, box_rows};
    cuuint32_t es[2] = {1, 1};
    enc(m, CU_TENSOR_MAP_DATA_TYPE_BFLOAT16, 2, const_cast<void*>(base), dims, strides, box, es,
        CU_TENSOR_MAP_INTERLEAVE_NONE, swz, (CUtensorMapL2promotion)promo, CU_TENSOR_MAP_FLOAT_OOB_FILL_NONE);
}

void encode3d(EncodeTiledFn enc, CUtensorMap* m, const void* base, uint64_t d0, uint64_t d1, uint64_t d2, uint64_t s1,
              uint64_t s2, uint32_t b0, uint32_t b1, uint32_t b2, CUtensorMapSwizzle swz) {
    cuuint64_t dims[3] = {d0, d1, d2};
    cuuint64_t strides[2] = {s1, s2};
    cuuint32_t box[3] = {b0, b1, b2};
    cuuint32_t es[3] = {1, 1, 1};
    CUresult r = enc(m, CU_TENSOR_MAP_DATA_TYPE_BFLOAT16, 3, const_cast<void*>(base), dims, strides, box, es,
        CU_TENSOR_MAP_INTERLEAVE_NONE, swz, CU_TENSOR_MAP_L2_PROMOTION_NONE, CU_TENSOR_MAP_FLOAT_OOB_FILL_NONE);
    (void)r;
}

}

extern "C" void kernel_launch(void* const* d_in, const int* in_sizes, int n_in, void* d_out, int out_size) {
    (void)in_sizes; (void)n_in; (void)out_size;
    void* fn = nullptr;
    cudaDriverEntryPointQueryResult qr;
    cudaGetDriverEntryPoint("cuTensorMapEncodeTiled", &fn, cudaEnableDefault, &qr);
    EncodeTiledFn enc = (EncodeTiledFn)fn;
    Maps maps;
    encode2d(enc, &maps.mod, d_in[9], D, 6 * D, 104, 72, CU_TENSOR_MAP_SWIZZLE_NONE, PROMO_MOD);
    encode3d(enc, &maps.wq, d_in[3], 64, D, 64, 4096 * 2, 128, 64, 32, 4, CU_TENSOR_MAP_SWIZZLE_128B);
    encode2d(enc, &maps.k, d_in[1], (uint64_t)NKV * SK, DH, 64, 64, CU_TENSOR_MAP_SWIZZLE_128B);
    encode2d(enc, &maps.v, d_in[2], (uint64_t)NKV * SK, DH, 64, 64, CU_TENSOR_MAP_SWIZZLE_128B);
    encode2d(enc, &maps.wo, d_in[4], 4096, D, 104, 64, CU_TENSOR_MAP_SWIZZLE_NONE, PROMO_WO);
    encode2d(enc, &maps.w1, d_in[6], D, FF, 56, 144, CU_TENSOR_MAP_SWIZZLE_NONE, PROMO_W1);
    encode3d(enc, &maps.w2, d_in[7], 192, 3, FF, 384, D * 2, 200, 3, 16, CU_TENSOR_MAP_SWIZZLE_NONE);

    cudaFuncSetAttribute(adaln_decode_kernel, cudaFuncAttributeMaxDynamicSharedMemorySize, SMEM_BYTES);
    cudaLaunchConfig_t cfg = {};
    cfg.gridDim = dim3(NKV * CS);
    cfg.blockDim = dim3(NTHREADS);
    cfg.dynamicSmemBytes = SMEM_BYTES;
    cfg.stream = cudaStreamPerThread;
    cudaLaunchAttribute at[1];
    at[0].id = cudaLaunchAttributeClusterDimension;
    at[0].val.clusterDim.x = CS;
    at[0].val.clusterDim.y = 1;
    at[0].val.clusterDim.z = 1;
    cfg.attrs = at;
    cfg.numAttrs = 1;
    Ptrs ptrs = {d_in[3], d_in[2], d_in[4], d_in[6], d_in[7]};
    cudaLaunchKernelEx(&cfg, adaln_decode_kernel, maps, ptrs, (const __nv_bfloat16*)d_in[1], (const __nv_bfloat16*)d_in[9], (const __nv_bfloat16*)d_in[0], (const __nv_bfloat16*)d_in[8],
                       (__nv_bfloat16*)d_out);
}
```

```cpp
#include <cuda.h>
#include <cuda_bf16.h>
#include <cuda_runtime.h>
#include <stdint.h>

namespace {

constexpr int D = 576, FF = 4608, NKV = 16, SK = 65536, WINDOW = 4096, DH = 128;
constexpr int CS = 6;
constexpr int NCW = 12;
constexpr int NCT = NCW * 32;
constexpr int MONW = 0;
constexpr int NTHREADS = NCT + 32 + MONW;
constexpr int MAXT = 11;

#define DEPTH_A 4
#define DEPTH_KV 4
#define DEPTH_WO 4
#define DEPTH_W1 4
#define DEPTH_W2 4
#define PACE_GBPS 3200
#define PACE_A PACE_GBPS
#define PACE_WO 3200
#define PACE_W1 2600
#define PACE_W1B 3200
#define W1_SPLIT 2
#define PACE_W2 3400
#define W2_EARLY 0
#define PACE_W2E PACE_W2
#define C1_DELAY 500
#define A1_DELAY 0
#define D1_DELAY 0
#define SOFT 0
#define SLIP -1
#define SOFT_FROM 8
#define SOFT_TAIL true
#define PACE_LEAD 0
#define TLB_WARM 0
#define PWAIT mbar_spin
#define POLL_SLEEP 0
#define PROMO_MOD 2
#define PROMO_WO 2
#define PROMO_W1 2
#define TMA_WARM 0
#define PROMO_W2 2
#define PREW 0
#define D1_DELAY2 0
#define KPRE_COST 0
#define KPREFETCH_BYTES (KPREFETCH * SZ_KV)
#define NFIRST 1
#define WQ_DELAY 0
#define KPREFETCH 0

constexpr int P_MOD = 208, P_WO = 208, P_W1 = 112, P_W2 = 208;
constexpr int SZ_MOD = 72 * P_MOD, SZ_WQ = 32 * 512, SZ_KV = 64 * 256, SZ_WO = 64 * P_WO, SZ_W1 = 144 * P_W1,
              SZ_W2 = 96 * P_W2;
constexpr int O_WQ = 0, O_MODA = O_WQ + 3 * SZ_WQ, O_MODB = O_MODA + SZ_MOD;
constexpr int P_GB = 48, SZ_GBT = D * P_GB, O_GBT = 0;
constexpr int O_WO = 0, O_W1A = O_WO + 4 * SZ_WO;
constexpr int O_RING = 95 * 1024, NRING = 6, NSLOT = 8;
constexpr int O_XSLOT = O_RING - 2 * SZ_KV;
constexpr int O_W1B = O_RING, O_W2 = O_W1B + 2 * SZ_W1;
constexpr int O_MISC = O_RING + NRING * SZ_KV;
static_assert(O_MODB + 2 * SZ_MOD <= O_RING && O_W1A + 2 * SZ_W1 <= O_RING, "area A");
static_assert(O_W2 + 3 * SZ_W2 <= O_MISC, "ring");
static_assert(O_XSLOT >= O_MODA && O_XSLOT % 1024 == 0 && O_XSLOT >= O_WO + 4 * SZ_WO, "extra slots");
__device__ __forceinline__ uint32_t slot_off(int slot) { return slot < NRING ? O_RING + slot * SZ_KV : O_XSLOT + (slot - NRING) * SZ_KV; }
constexpr int O_QBUF = O_MISC;
constexpr int O_OBUF = O_QBUF + 6144;
constexpr int O_MLBUF = O_OBUF + 6144;
constexpr int O_X2 = O_MLBUF + 128;
constexpr int O_G1P = O_X2 + 2304;
constexpr int O_SB = O_G1P + 2304;
constexpr int O_H1 = O_SB + 2304;
constexpr int O_XS = O_H1 + 2304;
constexpr int O_SC = O_XS + 2304;
constexpr int O_HV = O_SC + 1152;
constexpr int O_QV = O_HV + 256;
constexpr int PV_PITCH = 712;
constexpr int O_PV = O_QV + 512;
constexpr int O_OV = O_PV + 2944;
constexpr int O_H2 = O_OV + 512;
constexpr int O_RED1 = O_H2 + 1152;
constexpr int O_GA = O_RED1 + 768;
constexpr int O_GB = O_GA + 384;
constexpr int O_WMAX = O_GB + 384;
constexpr int O_WL = O_WMAX + 128;
constexpr int O_TAG = O_WL + 112;
constexpr int O_BAR = O_WL + 128;
constexpr int B_MODA = 0, B_WQ = 1, B_MODB = 4, B_K = 6, B_V = B_K + MAXT, B_WO = B_V + MAXT, B_W1 = B_WO + 4,
              B_W2 = B_W1 + 4, B_EMPTY = B_W2 + 3  , B_AFREE = B_EMPTY + 2 * MAXT, B_MODFREE = B_AFREE + 1, B_WOFREE = B_MODFREE + 1,
              B_GBT = B_WOFREE + 1, B_XQ = B_GBT + 1,
              B_XB = B_XQ + 1, B_XC = B_XB + 1, B_XG = B_XC + 1, B_XD = B_XG + 1, B_GATES = B_XD + 1,
              NBAR = B_GATES + 1;
constexpr int SMEM_BYTES = O_BAR + NBAR * 8;
static_assert(SMEM_BYTES <= 232448, "smem");

struct alignas(128) Scratch {
    uint4 a1[2 * 6 * 6 * 8 * 8];
    uint4 a2[4 * 6 * 6 * 4 * 8];
    uint4 c1[6 * 6 * 16 * 8];
    uint4 d1[6 * 6 * 16 * 8];
    unsigned epoch;
};
__device__ Scratch g_scr;

#define PROF(i) do {} while (0)
#define PROF1(i) do {} while (0)

__device__ __forceinline__ void mbar_init(uint32_t bar, uint32_t cnt) {
    asm volatile("mbarrier.init.shared::cta.b64 [%0], %1;" ::"r"(bar), "r"(cnt) : "memory");
}
__device__ __forceinline__ void mbar_expect_tx(uint32_t bar, uint32_t bytes) {
    asm volatile("mbarrier.arrive.expect_tx.shared::cta.b64 _, [%0], %1;" ::"r"(bar), "r"(bytes) : "memory");
}
__device__ __forceinline__ void mbar_arrive(uint32_t bar) {
    asm volatile("mbarrier.arrive.shared::cta.b64 _, [%0];" ::"r"(bar) : "memory");
}
__device__ __forceinline__ void mbar_wait(uint32_t bar) {
    uint32_t ok;
    int n = 0;
    do {
        asm volatile("{\n.reg .pred p;\nmbarrier.try_wait.parity.shared::cta.b64 p, [%1], 0;\nselp.u32 %0, 1, 0, p;\n}"
                     : "=r"(ok) : "r"(bar) : "memory");
        if (++n > (1 << 22)) __trap();
    } while (!ok);
}
__device__ __forceinline__ bool mbar_test(uint32_t bar) {
    uint32_t ok;
    asm volatile("{\n.reg .pred p;\nmbarrier.test_wait.parity.shared::cta.b64 p, [%1], 0;\nselp.u32 %0, 1, 0, p;\n}"
                 : "=r"(ok) : "r"(bar) : "memory");
    return ok;
}
__device__ __forceinline__ void mbar_spin(uint32_t bar) {
    uint32_t ok;
    int n = 0;
    do {
        asm volatile("{\n.reg .pred p;\nmbarrier.test_wait.parity.shared::cta.b64 p, [%1], 0;\nselp.u32 %0, 1, 0, p;\n}"
                     : "=r"(ok) : "r"(bar) : "memory");
        if (++n > (1 << 24)) __trap();
    } while (!ok);
}
__device__ __forceinline__ void mbar_wait_cluster(uint32_t bar) {
    uint32_t ok;
    int n = 0;
    do {
        asm volatile("{\n.reg .pred p;\nmbarrier.try_wait.parity.acquire.cluster.shared::cta.b64 p, [%1], 0;\nselp.u32 %0, 1, 0, p;\n}"
                     : "=r"(ok) : "r"(bar) : "memory");
        if (++n > (1 << 22)) __trap();
    } while (!ok);
}
__device__ __forceinline__ uint32_t gtime32() { uint32_t t; asm volatile("mov.u32 %0, %%globaltimer_lo;" : "=r"(t)); return t; }
__device__ __forceinline__ void bar_sync(int id, int n) { asm volatile("bar.sync %0, %1;" ::"r"(id), "r"(n) : "memory"); }
__device__ __forceinline__ void bar_arrive(int id, int n) { asm volatile("bar.arrive %0, %1;" ::"r"(id), "r"(n) : "memory"); }
__device__ __forceinline__ void tma2d(uint32_t dst, const CUtensorMap* m, int c0, int c1, uint32_t bar, uint64_t pol) {
    asm volatile("cp.async.bulk.tensor.2d.shared::cluster.global.mbarrier::complete_tx::bytes.L2::cache_hint [%0], [%1, {%3, %4}], [%2], %5;"
                 ::"r"(dst), "l"(m), "r"(bar), "r"(c0), "r"(c1), "l"(pol) : "memory");
}
__device__ __forceinline__ void tma3d(uint32_t dst, const CUtensorMap* m, int c0, int c1, int c2, uint32_t bar, uint64_t pol) {
    asm volatile("cp.async.bulk.tensor.3d.shared::cluster.global.mbarrier::complete_tx::bytes.L2::cache_hint [%0], [%1, {%3, %4, %5}], [%2], %6;"
                 ::"r"(dst), "l"(m), "r"(bar), "r"(c0), "r"(c1), "r"(c2), "l"(pol) : "memory");
}
__device__ __forceinline__ void tma_touch(const void* p) {
    asm volatile("cp.async.bulk.prefetch.L2.global [%0], 16;" ::"l"(p) : "memory");
}
__device__ __forceinline__ uint32_t mapa(uint32_t addr, uint32_t rank) {
    uint32_t r;
    asm("mapa.shared::cluster.u32 %0, %1, %2;" : "=r"(r) : "r"(addr), "r"(rank));
    return r;
}
__device__ __forceinline__ void st_async4(uint32_t addr, float a, float b, float c, float d, uint32_t bar) {
    asm volatile("st.async.weak.shared::cluster.mbarrier::complete_tx::bytes.v4.f32 [%0], {%1,%2,%3,%4}, [%5];"
                 ::"r"(addr), "f"(a), "f"(b), "f"(c), "f"(d), "r"(bar) : "memory");
}
__device__ __forceinline__ void st_async2(uint32_t addr, float a, float b, uint32_t bar) {
    asm volatile("st.async.weak.shared::cluster.mbarrier::complete_tx::bytes.v2.f32 [%0], {%1,%2}, [%3];"
                 ::"r"(addr), "f"(a), "f"(b), "r"(bar) : "memory");
}
__device__ __forceinline__ void st_async1(uint32_t addr, uint32_t v, uint32_t bar) {
    asm volatile("st.async.weak.shared::cluster.mbarrier::complete_tx::bytes.b32 [%0], %1, [%2];"
                 ::"r"(addr), "r"(v), "r"(bar) : "memory");
}
__device__ __forceinline__ void st_msg(uint4* p, float a, float b, uint32_t tag) {
    asm volatile("{\n.reg .b128 t;\n.reg .b64 lo, hi;\nmov.b64 lo, {%1,%2};\nmov.b64 hi, {%3,%3};\nmov.b128 t, {lo,hi};\n"
                 "st.relaxed.gpu.global.b128 [%0], t;\n}"
                 ::"l"(p), "r"(__float_as_uint(a)), "r"(__float_as_uint(b)), "r"(tag) : "memory");
}
__device__ __forceinline__ uint4 ld_msg(const uint4* p) {
    uint4 v;
    asm volatile("{\n.reg .b128 t;\n.reg .b64 lo, hi;\nld.relaxed.gpu.global.b128 t, [%4];\nmov.b128 {lo,hi}, t;\n"
                 "mov.b64 {%0,%1}, lo;\nmov.b64 {%2,%3}, hi;\n}"
                 : "=r"(v.x), "=r"(v.y), "=r"(v.z), "=r"(v.w) : "l"(p) : "memory");
    return v;
}
template <int N>
__device__ __forceinline__ float2 gather_msgs(const uint4* p, int stride, uint32_t tag) {
    uint4 v[N];
#pragma unroll
    for (int i = 0; i < N; i++) v[i] = ld_msg(p + i * stride);
    for (int n = 0;; n++) {
        bool ok = true;
#pragma unroll
        for (int i = 0; i < N; i++) ok = ok && (v[i].w == tag);
        if (__all_sync(0xffffffffu, ok)) break;
        if (POLL_SLEEP > 0) __nanosleep(POLL_SLEEP);
#pragma unroll
        for (int i = 0; i < N; i++) if (v[i].w != tag) v[i] = ld_msg(p + i * stride);
        if (n > (1 << 21)) __trap();
    }
    float a = __uint_as_float(v[0].x), b = __uint_as_float(v[0].y);
#pragma unroll
    for (int i = 1; i < N; i++) { a += __uint_as_float(v[i].x); b += __uint_as_float(v[i].y); }
    a += __shfl_xor_sync(0xffffffffu, a, 8);
    b += __shfl_xor_sync(0xffffffffu, b, 8);
    a += __shfl_xor_sync(0xffffffffu, a, 16);
    b += __shfl_xor_sync(0xffffffffu, b, 16);
    return make_float2(a, b);
}
__device__ __forceinline__ void gather_msgs2(const uint4* p, const uint4* q, uint32_t tag, float2& u, float2& w, uint32_t sm) {
    uint4 v[4];
    v[0] = ld_msg(p); v[1] = ld_msg(p + 32); v[2] = ld_msg(q); v[3] = ld_msg(q + 32);
    for (int n = 0;; n++) {
        const bool ok = v[0].w == tag && v[1].w == tag && v[2].w == tag && v[3].w == tag;
        if (__all_sync(0xffffffffu, ok)) break;
        if (POLL_SLEEP > 0) __nanosleep(POLL_SLEEP);
        if (v[0].w != tag) v[0] = ld_msg(p);
        if (v[1].w != tag) v[1] = ld_msg(p + 32);
        if (v[2].w != tag) v[2] = ld_msg(q);
        if (v[3].w != tag) v[3] = ld_msg(q + 32);
        if (n > (1 << 21)) __trap();
    }
    float a = __uint_as_float(v[0].x) + __uint_as_float(v[1].x), b = __uint_as_float(v[0].y) + __uint_as_float(v[1].y);
    float c = __uint_as_float(v[2].x) + __uint_as_float(v[3].x), d = __uint_as_float(v[2].y) + __uint_as_float(v[3].y);
#pragma unroll
    for (int o = 8; o <= 16; o <<= 1) {
        a += __shfl_xor_sync(0xffffffffu, a, o); b += __shfl_xor_sync(0xffffffffu, b, o);
        c += __shfl_xor_sync(0xffffffffu, c, o); d += __shfl_xor_sync(0xffffffffu, d, o);
    }
    u = make_float2(a, b);
    w = make_float2(c, d);
}
__device__ __forceinline__ void ldsm4(uint32_t (&a)[4], uint32_t addr) {
    asm volatile("ldmatrix.sync.aligned.m8n8.x4.shared.b16 {%0,%1,%2,%3}, [%4];"
                 : "=r"(a[0]), "=r"(a[1]), "=r"(a[2]), "=r"(a[3]) : "r"(addr) : "memory");
}
__device__ __forceinline__ void ldsm4t(uint32_t (&a)[4], uint32_t addr) {
    asm volatile("ldmatrix.sync.aligned.m8n8.x4.trans.shared.b16 {%0,%1,%2,%3}, [%4];"
                 : "=r"(a[0]), "=r"(a[1]), "=r"(a[2]), "=r"(a[3]) : "r"(addr) : "memory");
}
__device__ __forceinline__ void ldsm2t(uint32_t (&a)[2], uint32_t addr) {
    asm volatile("ldmatrix.sync.aligned.m8n8.x2.trans.shared.b16 {%0,%1}, [%2];"
                 : "=r"(a[0]), "=r"(a[1]) : "r"(addr) : "memory");
}
__device__ __forceinline__ void mma16(float (&c)[4], const uint32_t (&a)[4], uint32_t b0, uint32_t b1) {
    asm volatile("mma.sync.aligned.m16n8k16.row.col.f32.bf16.bf16.f32 {%0,%1,%2,%3}, {%4,%5,%6,%7}, {%8,%9}, {%0,%1,%2,%3};"
                 : "+f"(c[0]), "+f"(c[1]), "+f"(c[2]), "+f"(c[3])
                 : "r"(a[0]), "r"(a[1]), "r"(a[2]), "r"(a[3]), "r"(b0), "r"(b1));
}
__device__ __forceinline__ void mma8(float (&c)[4], const uint32_t (&a)[2], uint32_t b0) {
    asm volatile("mma.sync.aligned.m16n8k8.row.col.f32.bf16.bf16.f32 {%0,%1,%2,%3}, {%4,%5}, {%6}, {%0,%1,%2,%3};"
                 : "+f"(c[0]), "+f"(c[1]), "+f"(c[2]), "+f"(c[3]) : "r"(a[0]), "r"(a[1]), "r"(b0));
}
__device__ __forceinline__ uint32_t lds32(uint32_t a) { uint32_t v; asm volatile("ld.shared.b32 %0, [%1];" : "=r"(v) : "r"(a) : "memory"); return v; }
__device__ __forceinline__ uint2 lds64(uint32_t a) { uint2 v; asm volatile("ld.shared.v2.b32 {%0,%1}, [%2];" : "=r"(v.x), "=r"(v.y) : "r"(a) : "memory"); return v; }
__device__ __forceinline__ float ldsf(uint32_t a) { float v; asm volatile("ld.shared.f32 %0, [%1];" : "=f"(v) : "r"(a) : "memory"); return v; }
__device__ __forceinline__ float2 ldsf2(uint32_t a) { float2 v; asm volatile("ld.shared.v2.f32 {%0,%1}, [%2];" : "=f"(v.x), "=f"(v.y) : "r"(a) : "memory"); return v; }
__device__ __forceinline__ float4 ldsf4(uint32_t a) { float4 v; asm volatile("ld.shared.v4.f32 {%0,%1,%2,%3}, [%4];" : "=f"(v.x), "=f"(v.y), "=f"(v.z), "=f"(v.w) : "r"(a) : "memory"); return v; }
__device__ __forceinline__ uint4 lds128(uint32_t a) { uint4 v; asm volatile("ld.shared.v4.b32 {%0,%1,%2,%3}, [%4];" : "=r"(v.x), "=r"(v.y), "=r"(v.z), "=r"(v.w) : "r"(a) : "memory"); return v; }
__device__ __forceinline__ void sts128(uint32_t a, uint32_t x, uint32_t y, uint32_t z, uint32_t w) { asm volatile("st.shared.v4.b32 [%0], {%1,%2,%3,%4};" ::"r"(a), "r"(x), "r"(y), "r"(z), "r"(w) : "memory"); }
__device__ __forceinline__ void stsf(uint32_t a, float v) { asm volatile("st.shared.f32 [%0], %1;" ::"r"(a), "f"(v) : "memory"); }
__device__ __forceinline__ void stsf2(uint32_t a, float x, float y) { asm volatile("st.shared.v2.f32 [%0], {%1,%2};" ::"r"(a), "f"(x), "f"(y) : "memory"); }
__device__ __forceinline__ void sts32(uint32_t a, uint32_t v) { asm volatile("st.shared.b32 [%0], %1;" ::"r"(a), "r"(v) : "memory"); }
__device__ __forceinline__ uint32_t pack_bf16(float hi, float lo) {
    uint32_t r;
    asm("cvt.rn.bf16x2.f32 %0, %1, %2;" : "=r"(r) : "f"(hi), "f"(lo));
    return r;
}
__device__ __forceinline__ void sts_bf16(uint32_t a, float v) {
    asm volatile("st.shared.b16 [%0], %1;" ::"r"(a), "h"((unsigned short)pack_bf16(0.f, v)) : "memory");
}
__device__ __forceinline__ float bf16r(float x) { return __uint_as_float(pack_bf16(x, 0.f)); }
__device__ __forceinline__ float silu_bf16(float x) { return bf16r(__fdividef(x, 1.0f + __expf(-x))); }

template <int PITCH>
__device__ __forceinline__ uint32_t gemv_addr(uint32_t tile, int col0, int lane) {
    return tile + ((lane & 7) + 8 * (lane >> 4)) * PITCH + (col0 + 8 * ((lane >> 3) & 1)) * 2;
}
template <int PITCH, int NK>
__device__ __forceinline__ void gemv_tile(float (&acc0)[4], float (&acc1)[4], uint32_t a_addr, uint32_t v_addr) {
#pragma unroll
    for (int ks = 0; ks < NK; ks++) {
        uint32_t a[4];
        ldsm4t(a, a_addr + ks * 16 * PITCH);
        const uint32_t b0 = lds32(v_addr + ks * 32), b1 = lds32(v_addr + ks * 32 + 16);
        if (ks & 1) mma16(acc1, a, b0, b1); else mma16(acc0, a, b0, b1);
    }
}

__device__ __forceinline__ float2 ln_stats(const float (&x)[18], float shift) {
    float s1 = 0.f, s2 = 0.f, t1 = 0.f, t2 = 0.f, u1 = 0.f, u2 = 0.f;
#pragma unroll
    for (int i = 0; i < 18; i += 3) {
        const float d = x[i] - shift, e = x[i + 1] - shift, f = x[i + 2] - shift;
        s1 += d; s2 = fmaf(d, d, s2);
        t1 += e; t2 = fmaf(e, e, t2);
        u1 += f; u2 = fmaf(f, f, u2);
    }
    s1 += t1 + u1;
    s2 += t2 + u2;
#pragma unroll
    for (int o = 16; o; o >>= 1) { s1 += __shfl_xor_sync(0xffffffffu, s1, o); s2 += __shfl_xor_sync(0xffffffffu, s2, o); }
    const float md = s1 * (1.0f / D);
    const float var = fmaxf(s2 * (1.0f / D) - md * md, 0.f);
    const float mean = bf16r(shift + md);
    float sd, inv;
    asm("sqrt.approx.f32 %0, %1;" : "=f"(sd) : "f"(bf16r(bf16r(var) + 1e-5f)));
    asm("rcp.approx.f32 %0, %1;" : "=f"(inv) : "f"(bf16r(sd)));
    return make_float2(mean, inv);
}
__device__ __forceinline__ float ln_norm(float x, float2 st) { return bf16r(bf16r(x - st.x) * st.y); }
__device__ __forceinline__ float modulate(float xn, float g1p, float shift) { return bf16r(bf16r(xn * g1p) + shift); }

template <int LO, int HI>
__device__ __forceinline__ void init_barriers(uint32_t bars) {
#pragma unroll
    for (int i = LO; i < HI; i++)
        mbar_init(bars + i * 8, i < B_EMPTY ? 1 : i < B_EMPTY + MAXT ? 4 : i < B_AFREE ? 8 : i == B_AFREE ? 8 : i == B_MODFREE ? 10 : i == B_WOFREE ? 6 : 1);
}

struct Maps { CUtensorMap mod, wq, k, v, wo, w1, w2, gb; };
struct Ptrs { const void *wq, *v, *wo, *w1, *w2; };

__global__ void __launch_bounds__(NTHREADS, 1)
adaln_decode_kernel(const __grid_constant__ Maps maps, const __grid_constant__ Ptrs ptrs, const __nv_bfloat16* __restrict__ kbase,
                    const __nv_bfloat16* __restrict__ gmod,
                    const __nv_bfloat16* __restrict__ gx,
                    const __nv_bfloat16* __restrict__ gc, __nv_bfloat16* __restrict__ gout) {
    extern __shared__ __align__(1024) unsigned char smem_raw[];
    const uint32_t sm = (uint32_t)__cvta_generic_to_shared(smem_raw);
    const uint32_t bars = sm + O_BAR;
    const int tid = threadIdx.x, warp = tid >> 5, lane = tid & 31;
    uint32_t j;
    asm("mov.u32 %0, %%cluster_ctarank;" : "=r"(j));
    uint32_t hu;
    asm("mov.u32 %0, %%clusterid.x;" : "=r"(hu));
    const int h = (int)hu;
    const int nt = j < 4 ? 11 : 10;
    const int tile0 = j < 4 ? 11 * j : 44 + 10 * (j - 4);
#define BAR(i) (bars + (i) * 8)

    if (__builtin_expect(warp == NCW, 1)) {
        uint64_t pol;
        asm volatile("createpolicy.fractional.L2::evict_first.b64 %0, 1.0;" : "=l"(pol));
        if (lane == 0) PROF1(0);
        const uint32_t tstart = __shfl_sync(0xffffffffu, gtime32(), 0);
        if (lane == 0) {
            init_barriers<B_MODA, B_K>(bars);
            asm volatile("fence.mbarrier_init.release.cluster;" ::: "memory");
            mbar_expect_tx(BAR(B_MODA), SZ_MOD);
            tma2d(sm + O_MODA, &maps.mod, (h & 1) * D + 96 * j, (h >> 1) * 72, BAR(B_MODA), pol);
#pragma unroll
            for (int i = 0; i < NFIRST; i++) {
                mbar_expect_tx(BAR(B_WQ + i), SZ_WQ);
                tma3d(sm + O_WQ + i * SZ_WQ, &maps.wq, 0, 96 * j + i * 32, h * 4, BAR(B_WQ + i), pol);
            }
            PROF1(18);
        }
        __syncwarp();
        bar_arrive(0, NCT + 32);
        asm volatile("barrier.cluster.arrive.relaxed.aligned;" ::: "memory");
        bar_sync(3, 128 + MONW);
        if (lane != 0) return;
        uint32_t qm = 0, q0 = NFIRST > 2 ? BAR(B_WQ + NFIRST - 4) : 0, q1 = NFIRST > 1 ? BAR(B_WQ + NFIRST - 3) : 0,
                 q2 = NFIRST > 0 ? BAR(B_WQ + NFIRST - 2) : 0, q3 = BAR(B_WQ + NFIRST - 1);
#define MON() do {} while (0)
#define PACE(bytes_all, rate, softbar) { \
            uint32_t now_ = gtime32(); \
            while ((int)(now_ - due) < 0) now_ = gtime32(); \
            if (SOFT > 0 && soft_on && (softbar) && !mbar_test(softbar)) { \
                const uint32_t lim_ = now_ + SOFT; \
                do { now_ = gtime32(); } while (!mbar_test(softbar) && (int)(now_ - lim_) < 0); \
                due = now_; \
            } \
            if (SLIP >= 0 && (int)(now_ - due) > SLIP) due = now_ - (uint32_t)(SLIP < 0 ? 0 : SLIP); \
            due += (uint32_t)((bytes_all) / (rate)); }
#define STAGE_BEGIN(depth, bar_, bytes_all, rate) \
        { const uint32_t w_ = (depth) == 5 ? qm : (depth) == 4 ? q0 : (depth) == 3 ? q1 : q2; if (w_) PWAIT(w_); \
          const uint32_t s_ = (depth) == 5 ? q0 : (depth) == 4 ? q1 : (depth) == 3 ? q2 : q3; \
          qm = q0; q0 = q1; q1 = q2; q2 = q3; q3 = (bar_); PACE(bytes_all, rate, s_); }
        const int cb = h * CS + j;
        uint32_t due = tstart - PACE_LEAD + (D * 2 * D * 2 + NFIRST * (D * 4096 * 2 / 3)) / PACE_A;
        bool soft_on = false;
#pragma unroll 1
        for (int i = NFIRST; i < 3; i++) {
            const uint32_t b = BAR(B_WQ + i);
            STAGE_BEGIN(DEPTH_A, b, D * 4096 * 2 / 3, PACE_A);
            mbar_expect_tx(b, SZ_WQ);
            tma3d(sm + O_WQ + i * SZ_WQ, &maps.wq, 0, 96 * j + i * 32, h * 4, b, pol);
            MON();
        }
#pragma unroll 1
        for (int i = 0; i < 2; i++) {
            const uint32_t b = BAR(B_MODB + i);
            const bool real = (h & 3) != 3;
            if (real) {
                STAGE_BEGIN(DEPTH_A, b, D * 3 * D * 2 / 2, PACE_A);
                mbar_expect_tx(b, SZ_MOD);
                tma2d(sm + O_MODB + i * SZ_MOD, &maps.mod, (2 + (h & 3)) * D + 96 * j, (h >> 2) * 144 + i * 72, b, pol);
            } else {
                PACE(D * 3 * D * 2 / 2, PACE_A, 0u);
            }
            MON();
        }
        {
            const int row0 = h * SK + (SK - WINDOW) + tile0 * 64;
            int slot = 0;
#pragma unroll 1
            for (int n = 0; n < 2 * nt; n++) {
                const bool isv = n >= nt;
                const int t = isv ? n - nt : n;
                const uint32_t b = BAR((isv ? B_V : B_K) + t), dst = sm + slot_off(slot);
                const CUtensorMap* m = isv ? &maps.v : &maps.k;
                soft_on = n >= SOFT_FROM;
                const int kv_bytes = n < KPREFETCH ? KPRE_COST : nt == 11 ? NKV * WINDOW * DH * 4 / 22 : NKV * WINDOW * DH * 4 / 20;
                STAGE_BEGIN(DEPTH_KV, b, kv_bytes, PACE_GBPS);
                if (n == NRING) PWAIT(BAR(B_MODFREE));
                if (n >= NSLOT) { const int pn = n - NSLOT; PWAIT(BAR(B_EMPTY + (pn < nt ? pn : MAXT + pn - nt))); }
                mbar_expect_tx(b, SZ_KV);
                tma2d(dst, m, 0, row0 + t * 64, b, pol);
                tma2d(dst + 8192, m, 64, row0 + t * 64, b, pol);
                MON();
                slot = slot == NSLOT - 1 ? 0 : slot + 1;
                if (n == 0) PROF1(22);
                if (n == nt) PROF1(1);
            }
        }
        soft_on = SOFT_TAIL;
#pragma unroll 1
        for (int i = 0; i < 4; i++) {
            const uint32_t b = BAR(B_WO + i);
            STAGE_BEGIN(DEPTH_WO, b, D * 4096 * 2 / 4, PACE_WO);
            if (i == 0) { PWAIT(BAR(B_AFREE)); PWAIT(BAR(B_MODFREE)); PROF1(2); }
            mbar_expect_tx(b, SZ_WO);
            tma2d(sm + O_WO + i * SZ_WO, &maps.wo, 96 * j, h * 256 + i * 64, b, pol);
            MON();
        }
        auto issue_w2 = [&](int i, bool early) {
            const uint32_t b = BAR(B_W2 + i);
            if (early) { STAGE_BEGIN(DEPTH_W2, b, D * FF * 2 / 3, PACE_W2E); } else { STAGE_BEGIN(DEPTH_W2, b, D * FF * 2 / 3, PACE_W2); }
            if (early && i == 0) PWAIT(BAR(B_EMPTY + MAXT + nt - 1));
            mbar_expect_tx(b, SZ_W2);
            tma2d(sm + O_W2 + i * SZ_W2, &maps.w2, 96 * j, h * 288 + i * 96, b, pol);
            MON();
        };
#pragma unroll 1
        for (int i = 0; i < W2_EARLY; i++) issue_w2(i, true);
#pragma unroll 1
        for (int i = 0; i < 4; i++) {
            const uint32_t b = BAR(B_W1 + i);
            STAGE_BEGIN(DEPTH_W1, b, D * FF * 2 / 4, (i < W1_SPLIT ? PACE_W1 : PACE_W1B));
            if (i == 0) {
                PWAIT(BAR(B_EMPTY + MAXT + 14 - nt));
                PWAIT(BAR(B_EMPTY + MAXT + 15 - nt));
            }
            if (i == 2) PWAIT(BAR(B_EMPTY + MAXT + nt - 1));
            mbar_expect_tx(b, SZ_W1);
            tma2d(sm + (i < 2 ? O_W1A + i * SZ_W1 : O_W1B + (i - 2) * SZ_W1), &maps.w1, cb * 48, i * 144, b, pol);
            MON();
        }
#pragma unroll 1
        for (int i = W2_EARLY; i < 3; i++) issue_w2(i, false);
        PROF1(3);
        if (h < 6) {
            PWAIT(BAR(B_WOFREE));
            mbar_expect_tx(BAR(B_GBT), SZ_GBT);
#pragma unroll 1
            for (int i = 0; i < 3; i++)
                tma2d(sm + O_GBT + i * 192 * P_GB, &maps.gb, 5 * D + 96 * j + 16 * h, i * 192, BAR(B_GBT), pol);
        }
#undef STAGE_BEGIN
#undef MON
        asm volatile("barrier.cluster.wait;" ::: "memory");
        return;
    }

    const int g = lane >> 2, t4 = lane & 3;
    const int r7 = lane & 7, lg = lane >> 3;
    uint4* const a1_out = g_scr.a1 + ((((h & 1) * 6 + j) * 6) * 8 + (h >> 1)) * 8;
    uint4* const a2_out = g_scr.a2 + ((((h & 3) * 6 + j) * 6) * 4 + (h >> 2)) * 8;
    uint4* const c1_out = g_scr.c1 + ((j * 6) * 16 + h) * 8;
    uint4* const d1_out = g_scr.d1 + ((j * 6) * 16 + h) * 8;

    uint32_t xv = 0, cv = 0;
    if (warp >= 9) {
        if (lane == 0) {
            if (warp == 9) init_barriers<B_K, B_EMPTY>(bars);
            else if (warp == 10) init_barriers<B_EMPTY, B_AFREE>(bars);
            else {
                init_barriers<B_AFREE, NBAR>(bars);
                mbar_expect_tx(BAR(B_XQ), CS * 1024);
                mbar_expect_tx(BAR(B_XB), CS * 1040);
                mbar_expect_tx(BAR(B_XC), CS * 192);
                mbar_expect_tx(BAR(B_XG), CS * 768);
                mbar_expect_tx(BAR(B_XD), CS * 96);
            }
            asm volatile("fence.mbarrier_init.release.cluster;" ::: "memory");
        }
        __syncwarp();
        bar_arrive(3, 128 + MONW);
    } else {
        xv = __ldg(reinterpret_cast<const uint32_t*>(gx) + tid);
        cv = __ldg(reinterpret_cast<const uint32_t*>(gc) + tid);
    }
    uint32_t xall[9];
    uint32_t xc0 = 0, xc1 = 0;
    if (warp < 6) {
#pragma unroll
        for (int i = 0; i < 9; i++) xall[i] = __ldg(reinterpret_cast<const uint32_t*>(gx) + lane + 32 * i);
        xc0 = __ldg(reinterpret_cast<const unsigned short*>(gx) + 96 * j + warp * 16 + r7);
        xc1 = __ldg(reinterpret_cast<const unsigned short*>(gx) + 96 * j + warp * 16 + r7 + 8);
    }
    asm volatile("barrier.cluster.arrive.relaxed.aligned;" ::: "memory");
    uint32_t epoch = 0;
    if (tid == 288) epoch = *(volatile unsigned*)&g_scr.epoch;
    if (t4 == 0) {
        if (warp < 6) st_msg(a1_out + warp * 64 + g, 0.f, 0.f, 0);
        else if (warp >= 8) {
            st_msg(a2_out + (warp - 8) * 32 + g, 0.f, 0.f, 0);
            if (warp < 10) st_msg(a2_out + (warp - 4) * 32 + g, 0.f, 0.f, 0);
        }
    }
    if (tid < 288) {
        stsf2(sm + O_XS + tid * 8, __uint_as_float(xv << 16), __uint_as_float(xv & 0xffff0000u));
        const float c0 = silu_bf16(__uint_as_float(cv << 16)), c1 = silu_bf16(__uint_as_float(cv & 0xffff0000u));
        sts32(sm + O_SC + tid * 4, (__float_as_uint(c0) >> 16) | (__float_as_uint(c1) & 0xffff0000u));
    }
    if (tid == 288) sts32(sm + O_TAG, epoch + 1);
    float xn0 = 0.f, xn1 = 0.f;
    if (warp < 6) {
        float xr[18];
#pragma unroll
        for (int i = 0; i < 9; i++) { xr[2 * i] = __uint_as_float(xall[i] << 16); xr[2 * i + 1] = __uint_as_float(xall[i] & 0xffff0000u); }
        const float2 st = ln_stats(xr, __shfl_sync(0xffffffffu, xr[0], 0));
        xn0 = ln_norm(__uint_as_float(xc0 << 16), st);
        xn1 = ln_norm(__uint_as_float(xc1 << 16), st);
    }
    if (warp == 0) PROF(21);
    bar_sync(0, NCT + 32);
    const uint32_t tag = lds32(sm + O_TAG);
    if (tid == 6 * 32) {
        asm volatile("prefetch.tensormap [%0];" ::"l"(&maps.k) : "memory");
        asm volatile("prefetch.tensormap [%0];" ::"l"(&maps.v) : "memory");
    }
    if (tid == 7 * 32) {
        asm volatile("prefetch.tensormap [%0];" ::"l"(&maps.wo) : "memory");
        asm volatile("prefetch.tensormap [%0];" ::"l"(&maps.w1) : "memory");
        asm volatile("prefetch.tensormap [%0];" ::"l"(&maps.w2) : "memory");
    }
    if (warp == 0) PROF(4);

    if (warp < 6) {
        float acc0[4] = {0.f, 0.f, 0.f, 0.f}, acc1[4] = {0.f, 0.f, 0.f, 0.f};
        const uint32_t va = sm + O_SC + ((h >> 1) * 72 + 2 * t4) * 2;
        mbar_wait(BAR(B_MODA));
        if (warp == 0) PROF(19);
        gemv_tile<P_MOD, 4>(acc0, acc1, gemv_addr<P_MOD>(sm + O_MODA, warp * 16, lane), va);
        {
            uint32_t a[2];
            ldsm2t(a, sm + O_MODA + (64 + r7) * P_MOD + (warp * 16 + 8 * (lg & 1)) * 2);
            mma8(acc0, a, lds32(va + 128));
        }
        if (t4 == 0) st_msg(a1_out + warp * 64 + g, acc0[0] + acc1[0], acc0[2] + acc1[2], tag);
        if (lane == 0) mbar_arrive(BAR(B_MODFREE));
        if (warp == 0) PROF(5);
        const uint4* in = g_scr.a1 + (j * 6 + warp) * 64 + lane;
        float2 sa, ca;
        gather_msgs2(in, in + 36 * 64, tag, sa, ca, sm);
        if (lg == 0) {
            const int c = warp * 16 + r7;
            sts_bf16(sm + O_HV + c * 2, modulate(xn0, bf16r(1.f + bf16r(ca.x)), bf16r(sa.x)));
            sts_bf16(sm + O_HV + (c + 8) * 2, modulate(xn1, bf16r(1.f + bf16r(ca.y)), bf16r(sa.y)));
        }
        if (warp == 0) PROF(6);
    }
    asm volatile("barrier.cluster.wait.aligned;" ::: "memory");

    if (warp < 8) {
        bar_sync(1, 256);
        float a00[4] = {0.f, 0.f, 0.f, 0.f}, a01[4] = {0.f, 0.f, 0.f, 0.f};
        float a10[4] = {0.f, 0.f, 0.f, 0.f}, a11[4] = {0.f, 0.f, 0.f, 0.f};
        const uint32_t va = sm + O_HV + 4 * t4;
        const uint32_t a_off = (warp >> 1) * 4096 + (r7 + 8 * (lg >> 1)) * 128 + (((4 * (warp & 1) + (lg & 1)) ^ r7) << 4);
#pragma unroll
        for (int i = 0; i < 3; i++) {
            mbar_wait(BAR(B_WQ + i));
            if (i == 2 && warp == 4) PROF(20);
#pragma unroll
            for (int k2 = 0; k2 < 2; k2++) {
                const int ks = 2 * i + k2;
                const uint32_t b0 = lds32(va + ks * 32), b1 = lds32(va + ks * 32 + 16);
                uint32_t a[4];
                ldsm4t(a, sm + O_WQ + i * SZ_WQ + k2 * 2048 + a_off);
                if (k2) mma16(a01, a, b0, b1); else mma16(a00, a, b0, b1);
                ldsm4t(a, sm + O_WQ + i * SZ_WQ + k2 * 2048 + (a_off ^ 32));
                if (k2) mma16(a11, a, b0, b1); else mma16(a10, a, b0, b1);
            }
        }
        const uint32_t dst = sm + O_QBUF + j * 1024 + (warp * 8 + g) * 16;
        const float v0 = a00[0] + a01[0], v1 = a00[2] + a01[2], v2 = a10[0] + a11[0], v3 = a10[2] + a11[2];
        st_async4(mapa(dst, t4), v0, v1, v2, v3, mapa(BAR(B_XQ), t4));
        if (t4 < 2) st_async4(mapa(dst, t4 + 4), v0, v1, v2, v3, mapa(BAR(B_XQ), t4 + 4));
        if (lane == 0) mbar_arrive(BAR(B_AFREE));
        mbar_wait_cluster(BAR(B_XQ));
        float q = 0.f;
#pragma unroll
        for (int s = 0; s < CS; s++) q += ldsf(sm + O_QBUF + s * 1024 + tid * 4);
        const int e = tid & 3;
        const int n = warp * 32 + (e >> 1) * 16 + g + 8 * (e & 1);
        sts_bf16(sm + O_QV + n * 2, q);
    }
    if (warp >= 8) {
        if ((h & 3) != 3) {
            mbar_wait(BAR(B_MODB));
            mbar_wait(BAR(B_MODB + 1));
            const uint32_t va = sm + O_SC + ((h >> 2) * 144 + 2 * t4) * 2;
            for (int l = warp - 8; l < 6; l += 4) {
                float acc0[4] = {0.f, 0.f, 0.f, 0.f}, acc1[4] = {0.f, 0.f, 0.f, 0.f};
                gemv_tile<P_MOD, 9>(acc0, acc1, gemv_addr<P_MOD>(sm + O_MODB, l * 16, lane), va);
                if (t4 == 0) st_msg(a2_out + l * 32 + g, acc0[0] + acc1[0], acc0[2] + acc1[2], tag);
            }
            __syncwarp();
        }
        if (lane == 0) mbar_arrive(BAR(B_MODFREE));
    }

    bar_sync(2, NCT);
    if (warp == 0) PROF(7);
    uint32_t qb[16];
#pragma unroll
    for (int ks = 0; ks < 8; ks++) {
        const uint32_t a = sm + O_QV + ((g & 1) * 128 + ks * 16 + 2 * t4) * 2;
        qb[2 * ks] = lds32(a);
        qb[2 * ks + 1] = lds32(a + 16);
    }

    float sc[4];
    {
        const int grp = warp >> 2, mi = lg;
        const uint32_t a_off = (16 * (warp & 3) + r7 + 8 * (mi & 1)) * 128 + (((mi >> 1) ^ r7) << 4);
        float mx = -INFINITY;
#pragma unroll
        for (int it = 0; it < 4; it++) {
            const int t = grp + 3 * it;
            sc[it] = -INFINITY;
            if (t < nt) {
                mbar_wait(BAR(B_K + t));
                const uint32_t base = sm + slot_off(t % NSLOT);
                float c0[4] = {0.f, 0.f, 0.f, 0.f}, c1[4] = {0.f, 0.f, 0.f, 0.f};
#pragma unroll
                for (int ks = 0; ks < 8; ks++) {
                    uint32_t a[4];
                    ldsm4(a, base + (ks >> 2) * 8192 + (a_off ^ ((ks & 3) << 5)));
                    if (ks & 1) mma16(c1, a, qb[2 * ks], qb[2 * ks + 1]); else mma16(c0, a, qb[2 * ks], qb[2 * ks + 1]);
                }
                __syncwarp();
                if (lane == 0) mbar_arrive(BAR(B_EMPTY + t));
                const float v = t4 == 0 ? c0[0] + c1[0] : t4 == 1 ? c0[1] + c1[1] : t4 == 2 ? c0[2] + c1[2] : c0[3] + c1[3];
                sc[it] = bf16r(bf16r(v) * 0.08838834764831845f);
                mx = fmaxf(mx, sc[it]);
            }
        }
        mx = fmaxf(mx, __shfl_xor_sync(0xffffffffu, mx, 2));
        mx = fmaxf(mx, __shfl_xor_sync(0xffffffffu, mx, 4));
        mx = fmaxf(mx, __shfl_xor_sync(0xffffffffu, mx, 8));
        mx = fmaxf(mx, __shfl_xor_sync(0xffffffffu, mx, 16));
        if (lane < 2) stsf(sm + O_WMAX + (warp * 2 + lane) * 4, mx);
    }
    bar_sync(2, NCT);
    if (warp == 0) PROF(8);
    float cta_max;
    {
        const int hd = t4 & 1, grp = warp >> 2;
        float m = -INFINITY;
#pragma unroll
        for (int w = 0; w < NCW; w++) m = fmaxf(m, ldsf(sm + O_WMAX + (w * 2 + hd) * 4));
        cta_max = m;
        float l = 0.f;
#pragma unroll
        for (int it = 0; it < 4; it++) {
            const int t = grp + 3 * it;
            if (t < nt) {
                const float p = __expf(sc[it] - m);
                l += p;
                sts_bf16(sm + O_PV + (hd * PV_PITCH + t * 64 + 16 * (warp & 3) + g + 8 * (t4 >> 1)) * 2, p);
            }
        }
        l += __shfl_xor_sync(0xffffffffu, l, 2);
        l += __shfl_xor_sync(0xffffffffu, l, 4);
        l += __shfl_xor_sync(0xffffffffu, l, 8);
        l += __shfl_xor_sync(0xffffffffu, l, 16);
        if (lane < 2) stsf(sm + O_WL + (warp * 2 + lane) * 4, l);
    }
    if (warp < 6 && t4 == 0) {
        st_msg(c1_out + warp * 128 + g, 0.f, 0.f, 0);
        st_msg(d1_out + warp * 128 + g, 0.f, 0.f, 0);
    }
    bar_sync(2, NCT);

    if (warp >= 8) {
        const int m = warp - 8;
        if (m < 3) {
#pragma unroll 1
            for (int l = 0; l < 6; l++) {
                const float2 v = gather_msgs<1>(g_scr.a2 + ((m * 6 + j) * 6 + l) * 32 + lane, 0, tag);
                float a = bf16r(v.x), b = bf16r(v.y);
                if (m == 0) {
                    if (lg == 0) stsf2(sm + O_GA + (l * 8 + r7) * 8, a, b);
                } else {
                    if (m == 2) { a = bf16r(1.f + a); b = bf16r(1.f + b); }
                    const uint32_t dst = sm + (m == 1 ? O_SB : O_G1P) + ((j * 6 + l) * 8 + r7) * 8;
                    st_async2(mapa(dst, lg), a, b, mapa(BAR(B_XG), lg));
                    if (lg < 2) st_async2(mapa(dst, lg + 4), a, b, mapa(BAR(B_XG), lg + 4));
                }
            }
            __syncwarp();
            if (lane == 0 && m == 0) mbar_arrive(BAR(B_GATES));
        }
        if (warp == 8) {
            const float m0 = __shfl_sync(0xffffffffu, cta_max, 0), m1 = __shfl_sync(0xffffffffu, cta_max, 1);
            float l0 = 0.f, l1 = 0.f;
#pragma unroll
            for (int w = 0; w < NCW; w++) { const float2 v = ldsf2(sm + O_WL + w * 8); l0 += v.x; l1 += v.y; }
            if (lane < CS) st_async4(mapa(sm + O_MLBUF + j * 16, lane), m0, m1, l0, l1, mapa(BAR(B_XB), lane));
        }
    } else {
        const int mi = lg;
        const uint32_t a_off = (warp >> 2) * 8192 + (r7 + 8 * (mi >> 1)) * 128 + (((2 * (warp & 3) + (mi & 1)) ^ r7) << 4);
        const uint32_t pa = sm + O_PV + ((g & 1) * PV_PITCH + 2 * t4) * 2;
        float c0[4] = {0.f, 0.f, 0.f, 0.f}, c1[4] = {0.f, 0.f, 0.f, 0.f};
#pragma unroll 1
        for (int t = 0; t < nt; t++) {
            uint32_t b[8];
#pragma unroll
            for (int ks = 0; ks < 4; ks++) { b[2 * ks] = lds32(pa + (t * 64 + ks * 16) * 2); b[2 * ks + 1] = lds32(pa + (t * 64 + ks * 16) * 2 + 16); }
            mbar_wait(BAR(B_V + t));
            const uint32_t base = sm + slot_off((nt + t) % NSLOT) + a_off;
#pragma unroll
            for (int ks = 0; ks < 4; ks++) {
                uint32_t a[4];
                ldsm4t(a, base + ks * 2048);
                if (ks & 1) mma16(c1, a, b[2 * ks], b[2 * ks + 1]); else mma16(c0, a, b[2 * ks], b[2 * ks + 1]);
            }
            __syncwarp();
            if (lane == 0) mbar_arrive(BAR(B_EMPTY + MAXT + t));
        }
        if (warp == 0) PROF(9);
        const uint32_t dst = sm + O_OBUF + j * 1024 + (warp * 8 + g) * 16;
        const float v0 = c0[0] + c1[0], v1 = c0[1] + c1[1], v2 = c0[2] + c1[2], v3 = c0[3] + c1[3];
        st_async4(mapa(dst, t4), v0, v1, v2, v3, mapa(BAR(B_XB), t4));
        if (t4 < 2) st_async4(mapa(dst, t4 + 4), v0, v1, v2, v3, mapa(BAR(B_XB), t4 + 4));
        mbar_wait_cluster(BAR(B_XB));
        {
            const int e = tid & 3, hd = e & 1;
            float ms[CS], ls[CS], M = -INFINITY;
#pragma unroll
            for (int s = 0; s < CS; s++) {
                const float4 v = ldsf4(sm + O_MLBUF + s * 16);
                ms[s] = hd ? v.y : v.x; ls[s] = hd ? v.w : v.z;
                M = fmaxf(M, ms[s]);
            }
            float L = 0.f, o = 0.f;
#pragma unroll
            for (int s = 0; s < CS; s++) {
                const float w = __expf(ms[s] - M);
                L = fmaf(w, ls[s], L);
                o = fmaf(w, ldsf(sm + O_OBUF + s * 1024 + tid * 4), o);
            }
            const int n = hd * 128 + warp * 16 + g + 8 * (e >> 1);
            sts_bf16(sm + O_OV + n * 2, o / L);
        }
        bar_sync(1, 256);
        if (warp == 0) PROF(10);
        if (warp < 6) {
            float acc0[4] = {0.f, 0.f, 0.f, 0.f}, acc1[4] = {0.f, 0.f, 0.f, 0.f};
            const uint32_t va = sm + O_OV + 4 * t4;
#pragma unroll
            for (int i = 0; i < 4; i++) {
                mbar_wait(BAR(B_WO + i));
                gemv_tile<P_WO, 4>(acc0, acc1, gemv_addr<P_WO>(sm + O_WO + i * SZ_WO, warp * 16, lane), va + i * 128);
            }
            if (t4 == 0) st_msg(c1_out + warp * 128 + g, acc0[0] + acc1[0], acc0[2] + acc1[2], tag);
            if (lane == 0) mbar_arrive(BAR(B_WOFREE));
            if (warp == 0) PROF(11);
            const int c = 96 * j + warp * 16 + r7;
            const float x0 = ldsf(sm + O_XS + c * 4), x1 = ldsf(sm + O_XS + (c + 8) * 4);
            mbar_wait(BAR(B_GATES));
            mbar_wait_cluster(BAR(B_XG));
            const float2 ga = ldsf2(sm + O_GA + (warp * 8 + r7) * 8);
            { const uint32_t t0 = gtime32(); while ((int)(gtime32() - t0) < C1_DELAY) {} }
            const float2 at = gather_msgs<4>(g_scr.c1 + (j * 6 + warp) * 128 + lane, 32, tag);
            if (warp == 0) PROF(26);
            const float y0 = x0 + bf16r(ga.x * bf16r(at.x)), y1 = x1 + bf16r(ga.y * bf16r(at.y));
            const uint32_t xp = pack_bf16(y1, y0), dst2 = sm + O_X2 + ((j * 6 + warp) * 8 + r7) * 4;
            st_async1(mapa(dst2, lg), xp, mapa(BAR(B_XC), lg));
            if (lg < 2) st_async1(mapa(dst2, lg + 4), xp, mapa(BAR(B_XC), lg + 4));
            if (warp == 0) PROF(12);
        }
    }

    if (warp >= 6 && warp < 9) mbar_wait_cluster(BAR(B_XG));
    float2 g1 = make_float2(0.f, 0.f), sb = make_float2(0.f, 0.f);
    if (tid < 288) { g1 = ldsf2(sm + O_G1P + tid * 8); sb = ldsf2(sm + O_SB + tid * 8); }
    const int mt1 = warp % 3, kq = warp / 3;
    uint32_t wa[9][4];
    {
        const uint32_t a_addr = gemv_addr<P_W1>(sm + (kq < 2 ? O_W1A + kq * SZ_W1 : O_W1B + (kq - 2) * SZ_W1), mt1 * 16, lane);
        mbar_wait(BAR(B_W1 + kq));
        if (warp == 9) PROF(23);
#pragma unroll
        for (int ks = 0; ks < 9; ks++) ldsm4t(wa[ks], a_addr + ks * 16 * P_W1);
    }
    if (warp < 9) {
        mbar_wait_cluster(BAR(B_XC));
        uint32_t xp[9];
#pragma unroll
        for (int i = 0; i < 9; i++) xp[i] = lds32(sm + O_X2 + (lane + 32 * i) * 4);
        const uint32_t mine = lds32(sm + O_X2 + tid * 4);
        float xr[18];
#pragma unroll
        for (int i = 0; i < 9; i++) { xr[2 * i] = __uint_as_float(xp[i] << 16); xr[2 * i + 1] = __uint_as_float(xp[i] & 0xffff0000u); }
        const float2 st = ln_stats(xr, __shfl_sync(0xffffffffu, xr[0], 0));
        const float x0 = __uint_as_float(mine << 16), x1 = __uint_as_float(mine & 0xffff0000u);
        const int kk = tid & 7;
        const uint32_t dst = sm + O_H2 + ((tid >> 3) * 16 + (kk >> 1) * 4 + (kk & 1)) * 2;
        sts_bf16(dst, modulate(ln_norm(x0, st), g1.x, sb.x));
        sts_bf16(dst + 4, modulate(ln_norm(x1, st), g1.y, sb.y));
    }
    bar_sync(2, NCT);
    if (warp == 0) PROF(13);
    {
        float acc0[4] = {0.f, 0.f, 0.f, 0.f}, acc1[4] = {0.f, 0.f, 0.f, 0.f}, acc2[4] = {0.f, 0.f, 0.f, 0.f};
        const uint32_t va = sm + O_H2 + (kq * 144 + 4 * t4) * 2;
        uint2 bb[9];
#pragma unroll
        for (int ks = 0; ks < 9; ks++) bb[ks] = lds64(va + ks * 32);
#pragma unroll
        for (int ks = 0; ks < 9; ks += 3) {
            mma16(acc0, wa[ks], bb[ks].x, bb[ks].y);
            mma16(acc1, wa[ks + 1], bb[ks + 1].x, bb[ks + 1].y);
            mma16(acc2, wa[ks + 2], bb[ks + 2].x, bb[ks + 2].y);
        }
        if (t4 == 0) {
            stsf(sm + O_RED1 + (kq * 48 + mt1 * 16 + g) * 4, acc0[0] + acc1[0] + acc2[0]);
            stsf(sm + O_RED1 + (kq * 48 + mt1 * 16 + g + 8) * 4, acc0[2] + acc1[2] + acc2[2]);
        }
    }
    bar_sync(2, NCT);
    if (warp == 0) PROF(14);

    if (warp == 6) {
        const int pi = lane < 24 ? lane : 0;
        float2 s = ldsf2(sm + O_RED1 + pi * 8);
#pragma unroll
        for (int q = 1; q < 4; q++) { const float2 v = ldsf2(sm + O_RED1 + q * 192 + pi * 8); s.x += v.x; s.y += v.y; }
        const uint32_t pk = pack_bf16(silu_bf16(bf16r(s.y)), silu_bf16(bf16r(s.x)));
        const uint32_t dst = sm + O_H1 + j * 96 + ((pi >> 3) * 8 + (pi & 3) * 2 + ((pi >> 2) & 1)) * 4;
        if (lane < 24) {
#pragma unroll
            for (int d = 0; d < CS; d++) st_async1(mapa(dst, d), pk, mapa(BAR(B_XD), d));
        }
    }
    if (warp >= 6) {
        if (h < 6) {
            float acc0[4] = {0.f, 0.f, 0.f, 0.f}, acc1[4] = {0.f, 0.f, 0.f, 0.f};
            const int k = warp - 6;
            mbar_wait(BAR(B_GBT));
            gemv_tile<P_GB, 6>(acc0, acc1, gemv_addr<P_GB>(sm + O_GBT + k * 96 * P_GB, 0, lane), sm + O_SC + (k * 96 + 2 * t4) * 2);
            if (t4 == 0) {
                stsf(sm + O_GB + (k * 16 + g) * 4, acc0[0] + acc1[0]);
                stsf(sm + O_GB + (k * 16 + g + 8) * 4, acc0[2] + acc1[2]);
            }
            __syncwarp();
            bar_arrive(4, 7 * 32);
        }
    } else {
        const uint32_t a_addr = gemv_addr<P_W2>(sm + O_W2, warp * 16, lane);
        mbar_wait_cluster(BAR(B_XD));
        uint2 bb[18];
#pragma unroll
        for (int ks = 0; ks < 18; ks++) bb[ks] = lds64(sm + O_H1 + ks * 32 + t4 * 8);
        float acc[3][4];
#pragma unroll
        for (int i = 0; i < 3; i++) acc[i][0] = acc[i][1] = acc[i][2] = acc[i][3] = 0.f;
#pragma unroll
        for (int i = 0; i < 3; i++) {
            mbar_wait(BAR(B_W2 + i));
            if (warp == 0 && i == 0) PROF(24);
            if (warp == 0 && i == 2) PROF(25);
#pragma unroll
            for (int k = 0; k < 6; k++) {
                uint32_t a[4];
                ldsm4t(a, a_addr + (i * 6 + k) * 16 * P_W2);
                mma16(acc[k % 3], a, bb[i * 6 + k].x, bb[i * 6 + k].y);
            }
        }
        if (t4 == 0) st_msg(d1_out + warp * 128 + g, acc[0][0] + acc[1][0] + acc[2][0], acc[0][2] + acc[1][2] + acc[2][2], tag);
        if (warp == 0) PROF(16);
        if (warp == h) {
            const uint32_t xp = lds32(sm + O_X2 + ((j * 6 + warp) * 8 + r7) * 4);
            const float2 x2 = make_float2(__uint_as_float(xp << 16), __uint_as_float(xp & 0xffff0000u));
            const float2 y = gather_msgs<4>(g_scr.d1 + (j * 6 + warp) * 128 + lane, 32, tag);
            PROF(15);
            bar_sync(4, 7 * 32);
            PROF(28);
            float gb0 = 0.f, gb1 = 0.f;
#pragma unroll
            for (int k = 0; k < 6; k++) { gb0 += ldsf(sm + O_GB + (k * 16 + r7) * 4); gb1 += ldsf(sm + O_GB + (k * 16 + r7 + 8) * 4); }
            if (lg == 0) {
                const int c = 96 * j + warp * 16 + r7;
                const uint32_t o2 = pack_bf16(x2.y + bf16r(bf16r(gb1) * bf16r(y.y)), x2.x + bf16r(bf16r(gb0) * bf16r(y.x)));
                gout[c] = __ushort_as_bfloat16((unsigned short)o2);
                gout[c + 8] = __ushort_as_bfloat16((unsigned short)(o2 >> 16));
            }
            if (blockIdx.x == 0 && lane == 0) *(volatile unsigned*)&g_scr.epoch = tag;
            PROF(17);
        }
    }
#undef BAR
}

typedef CUresult (*EncodeTiledFn)(CUtensorMap*, CUtensorMapDataType, cuuint32_t, void*, const cuuint64_t*,
                                  const cuuint64_t*, const cuuint32_t*, const cuuint32_t*, CUtensorMapInterleave,
                                  CUtensorMapSwizzle, CUtensorMapL2promotion, CUtensorMapFloatOOBfill);

void encode2d(EncodeTiledFn enc, CUtensorMap* m, const void* base, uint64_t rows, uint64_t cols, uint32_t box_cols,
              uint32_t box_rows, CUtensorMapSwizzle swz, int promo = 0) {
    cuuint64_t dims[2] = {cols, rows};
    cuuint64_t strides[1] = {cols * 2};
    cuuint32_t box[2] = {box_cols, box_rows};
    cuuint32_t es[2] = {1, 1};
    enc(m, CU_TENSOR_MAP_DATA_TYPE_BFLOAT16, 2, const_cast<void*>(base), dims, strides, box, es,
        CU_TENSOR_MAP_INTERLEAVE_NONE, swz, (CUtensorMapL2promotion)promo, CU_TENSOR_MAP_FLOAT_OOB_FILL_NONE);
}

void encode3d(EncodeTiledFn enc, CUtensorMap* m, const void* base, uint64_t d0, uint64_t d1, uint64_t d2, uint64_t s1,
              uint64_t s2, uint32_t b0, uint32_t b1, uint32_t b2, CUtensorMapSwizzle swz) {
    cuuint64_t dims[3] = {d0, d1, d2};
    cuuint64_t strides[2] = {s1, s2};
    cuuint32_t box[3] = {b0, b1, b2};
    cuuint32_t es[3] = {1, 1, 1};
    CUresult r = enc(m, CU_TENSOR_MAP_DATA_TYPE_BFLOAT16, 3, const_cast<void*>(base), dims, strides, box, es,
        CU_TENSOR_MAP_INTERLEAVE_NONE, swz, CU_TENSOR_MAP_L2_PROMOTION_NONE, CU_TENSOR_MAP_FLOAT_OOB_FILL_NONE);
    (void)r;
}

}

extern "C" void kernel_launch(void* const* d_in, const int* in_sizes, int n_in, void* d_out, int out_size) {
    (void)in_sizes; (void)n_in; (void)out_size;
    void* fn = nullptr;
    cudaDriverEntryPointQueryResult qr;
    cudaGetDriverEntryPoint("cuTensorMapEncodeTiled", &fn, cudaEnableDefault, &qr);
    EncodeTiledFn enc = (EncodeTiledFn)fn;
    Maps maps;
    encode2d(enc, &maps.mod, d_in[9], D, 6 * D, 104, 72, CU_TENSOR_MAP_SWIZZLE_NONE, PROMO_MOD);
    encode3d(enc, &maps.wq, d_in[3], 64, D, 64, 4096 * 2, 128, 64, 32, 4, CU_TENSOR_MAP_SWIZZLE_128B);
    encode2d(enc, &maps.k, d_in[1], (uint64_t)NKV * SK, DH, 64, 64, CU_TENSOR_MAP_SWIZZLE_128B);
    encode2d(enc, &maps.v, d_in[2], (uint64_t)NKV * SK, DH, 64, 64, CU_TENSOR_MAP_SWIZZLE_128B);
    encode2d(enc, &maps.gb, d_in[9], D, 6 * D, 24, 192, CU_TENSOR_MAP_SWIZZLE_NONE, PROMO_MOD);
    encode2d(enc, &maps.wo, d_in[4], 4096, D, 104, 64, CU_TENSOR_MAP_SWIZZLE_NONE, PROMO_WO);
    encode2d(enc, &maps.w1, d_in[6], D, FF, 56, 144, CU_TENSOR_MAP_SWIZZLE_NONE, PROMO_W1);
    encode2d(enc, &maps.w2, d_in[7], FF, D, 104, 96, CU_TENSOR_MAP_SWIZZLE_NONE, PROMO_W2);

    cudaFuncSetAttribute(adaln_decode_kernel, cudaFuncAttributeMaxDynamicSharedMemorySize, SMEM_BYTES);
    cudaLaunchConfig_t cfg = {};
    cfg.gridDim = dim3(NKV * CS);
    cfg.blockDim = dim3(NTHREADS);
    cfg.dynamicSmemBytes = SMEM_BYTES;
    cfg.stream = cudaStreamPerThread;
    cudaLaunchAttribute at[1];
    at[0].id = cudaLaunchAttributeClusterDimension;
    at[0].val.clusterDim.x = CS;
    at[0].val.clusterDim.y = 1;
    at[0].val.clusterDim.z = 1;
    cfg.attrs = at;
    cfg.numAttrs = 1;
    Ptrs ptrs = {d_in[3], d_in[2], d_in[4], d_in[6], d_in[7]};
    cudaLaunchKernelEx(&cfg, adaln_decode_kernel, maps, ptrs, (const __nv_bfloat16*)d_in[1], (const __nv_bfloat16*)d_in[9], (const __nv_bfloat16*)d_in[0], (const __nv_bfloat16*)d_in[8],
                       (__nv_bfloat16*)d_out);
}
```

```cpp
#include <cuda.h>
#include <cuda_bf16.h>
#include <cuda_runtime.h>
#include <stdint.h>

namespace {

constexpr int D = 576, FF = 4608, NKV = 16, SK = 65536, WINDOW = 4096, DH = 128;
constexpr int CS = 6;
constexpr int NCW = 12;
constexpr int NCT = NCW * 32;
constexpr int NTHREADS = NCT + 32;
constexpr int MAXT = 11;

#define PACE_GBPS 3240
#define PACE_A PACE_GBPS
#define PACE_WO PACE_GBPS
#define PACE_W1 3000
#define PACE_W1B 3200
#define PACE_W2 3400
#define DEPTH 4
#define SOFT 40
#define SOFT_FROM 8
#define STAGGER 16
#define C1_DELAY 500

constexpr int P_MOD = 208, P_WO = 208, P_W1 = 112, P_W2 = 208;
constexpr int SZ_MOD = 72 * P_MOD, SZ_WQ = 32 * 512, SZ_KV = 64 * 256, SZ_WO = 64 * P_WO, SZ_W1 = 144 * P_W1,
              SZ_W2 = 96 * P_W2;
constexpr int O_WQ = 0, O_MODA = O_WQ + 3 * SZ_WQ, O_MODB = O_MODA + SZ_MOD;
constexpr int P_GB = 48, SZ_GBT = D * P_GB, O_GBT = 0;
constexpr int O_WO = 0, O_W1A = O_WO + 4 * SZ_WO;
constexpr int O_RING = 95 * 1024, NRING = 6, NSLOT = 8;
constexpr int O_XSLOT = O_RING - 2 * SZ_KV;
constexpr int O_W1B = O_RING, O_W2 = O_W1B + 2 * SZ_W1;
constexpr int O_MISC = O_RING + NRING * SZ_KV;
static_assert(O_MODB + 2 * SZ_MOD <= O_RING && O_W1A + 2 * SZ_W1 <= O_RING, "area A");
static_assert(O_W2 + 3 * SZ_W2 <= O_MISC, "ring");
static_assert(O_XSLOT >= O_MODA && O_XSLOT % 1024 == 0 && O_XSLOT >= O_WO + 4 * SZ_WO, "extra slots");
__device__ __forceinline__ uint32_t slot_off(int slot) { return slot < NRING ? O_RING + slot * SZ_KV : O_XSLOT + (slot - NRING) * SZ_KV; }
constexpr int O_QBUF = O_MISC;
constexpr int O_OBUF = O_QBUF + 6144;
constexpr int O_MLBUF = O_OBUF + 6144;
constexpr int O_X2 = O_MLBUF + 128;
constexpr int O_G1P = O_X2 + 2304;
constexpr int O_SB = O_G1P + 2304;
constexpr int O_H1 = O_SB + 2304;
constexpr int O_XS = O_H1 + 2304;
constexpr int O_SC = O_XS + 2304;
constexpr int O_HV = O_SC + 1152;
constexpr int O_QV = O_HV + 256;
constexpr int PV_PITCH = 712;
constexpr int O_PV = O_QV + 512;
constexpr int O_OV = O_PV + 2944;
constexpr int O_H2 = O_OV + 512;
constexpr int O_RED1 = O_H2 + 1152;
constexpr int O_GA = O_RED1 + 768;
constexpr int O_GB = O_GA + 384;
constexpr int O_WMAX = O_GB + 384;
constexpr int O_WL = O_WMAX + 128;
constexpr int O_TAG = O_WL + 112;
constexpr int O_BAR = O_WL + 128;
constexpr int B_MODA = 0, B_WQ = 1, B_MODB = 4, B_K = 6, B_V = B_K + MAXT, B_WO = B_V + MAXT, B_W1 = B_WO + 4,
              B_W2 = B_W1 + 4,
              B_EMPTY = B_W2 + 3  , B_AFREE = B_EMPTY + 2 * MAXT, B_MODFREE = B_AFREE + 1,
              B_WOFREE = B_MODFREE + 1,
              B_GBT = B_WOFREE + 1, B_XQ = B_GBT + 1,
              B_XB = B_XQ + 1, B_XC = B_XB + 1, B_XG = B_XC + 1, B_XD = B_XG + 1, B_GATES = B_XD + 1,
              NBAR = B_GATES + 1;
constexpr int SMEM_BYTES = O_BAR + NBAR * 8;
static_assert(SMEM_BYTES <= 232448, "smem");

struct alignas(128) Scratch {
    uint4 a1[2 * 6 * 6 * 8 * 8];
    uint4 a2[4 * 6 * 6 * 4 * 8];
    uint4 c1[6 * 6 * 16 * 8];
    uint4 d1[6 * 6 * 16 * 8];
    unsigned epoch;
};
__device__ Scratch g_scr;

__device__ __forceinline__ void mbar_init(uint32_t bar, uint32_t cnt) {
    asm volatile("mbarrier.init.shared::cta.b64 [%0], %1;" ::"r"(bar), "r"(cnt) : "memory");
}
__device__ __forceinline__ void mbar_expect_tx(uint32_t bar, uint32_t bytes) {
    asm volatile("mbarrier.arrive.expect_tx.shared::cta.b64 _, [%0], %1;" ::"r"(bar), "r"(bytes) : "memory");
}
__device__ __forceinline__ void mbar_arrive(uint32_t bar) {
    asm volatile("mbarrier.arrive.shared::cta.b64 _, [%0];" ::"r"(bar) : "memory");
}
__device__ __forceinline__ void mbar_wait(uint32_t bar) {
    uint32_t ok;
    int n = 0;
    do {
        asm volatile("{\n.reg .pred p;\nmbarrier.try_wait.parity.shared::cta.b64 p, [%1], 0;\nselp.u32 %0, 1, 0, p;\n}"
                     : "=r"(ok) : "r"(bar) : "memory");
        if (++n > (1 << 22)) __trap();
    } while (!ok);
}
__device__ __forceinline__ bool mbar_test(uint32_t bar) {
    uint32_t ok;
    asm volatile("{\n.reg .pred p;\nmbarrier.test_wait.parity.shared::cta.b64 p, [%1], 0;\nselp.u32 %0, 1, 0, p;\n}"
                 : "=r"(ok) : "r"(bar) : "memory");
    return ok;
}
__device__ __forceinline__ void mbar_spin(uint32_t bar) {
    uint32_t ok;
    int n = 0;
    do {
        asm volatile("{\n.reg .pred p;\nmbarrier.test_wait.parity.shared::cta.b64 p, [%1], 0;\nselp.u32 %0, 1, 0, p;\n}"
                     : "=r"(ok) : "r"(bar) : "memory");
        if (++n > (1 << 24)) __trap();
    } while (!ok);
}
__device__ __forceinline__ void mbar_wait_cluster(uint32_t bar) {
    uint32_t ok;
    int n = 0;
    do {
        asm volatile("{\n.reg .pred p;\nmbarrier.try_wait.parity.acquire.cluster.shared::cta.b64 p, [%1], 0;\nselp.u32 %0, 1, 0, p;\n}"
                     : "=r"(ok) : "r"(bar) : "memory");
        if (++n > (1 << 22)) __trap();
    } while (!ok);
}
__device__ __forceinline__ uint32_t gtime32() { uint32_t t; asm volatile("mov.u32 %0, %%globaltimer_lo;" : "=r"(t)); return t; }
__device__ __forceinline__ void bar_sync(int id, int n) { asm volatile("bar.sync %0, %1;" ::"r"(id), "r"(n) : "memory"); }
__device__ __forceinline__ void bar_arrive(int id, int n) { asm volatile("bar.arrive %0, %1;" ::"r"(id), "r"(n) : "memory"); }
__device__ __forceinline__ void tma2d(uint32_t dst, const CUtensorMap* m, int c0, int c1, uint32_t bar, uint64_t pol) {
    asm volatile("cp.async.bulk.tensor.2d.shared::cluster.global.mbarrier::complete_tx::bytes.L2::cache_hint [%0], [%1, {%3, %4}], [%2], %5;"
                 ::"r"(dst), "l"(m), "r"(bar), "r"(c0), "r"(c1), "l"(pol) : "memory");
}
__device__ __forceinline__ void tma3d(uint32_t dst, const CUtensorMap* m, int c0, int c1, int c2, uint32_t bar, uint64_t pol) {
    asm volatile("cp.async.bulk.tensor.3d.shared::cluster.global.mbarrier::complete_tx::bytes.L2::cache_hint [%0], [%1, {%3, %4, %5}], [%2], %6;"
                 ::"r"(dst), "l"(m), "r"(bar), "r"(c0), "r"(c1), "r"(c2), "l"(pol) : "memory");
}
__device__ __forceinline__ uint32_t mapa(uint32_t addr, uint32_t rank) {
    uint32_t r;
    asm("mapa.shared::cluster.u32 %0, %1, %2;" : "=r"(r) : "r"(addr), "r"(rank));
    return r;
}
__device__ __forceinline__ void st_async4(uint32_t addr, float a, float b, float c, float d, uint32_t bar) {
    asm volatile("st.async.weak.shared::cluster.mbarrier::complete_tx::bytes.v4.f32 [%0], {%1,%2,%3,%4}, [%5];"
                 ::"r"(addr), "f"(a), "f"(b), "f"(c), "f"(d), "r"(bar) : "memory");
}
__device__ __forceinline__ void st_async2(uint32_t addr, float a, float b, uint32_t bar) {
    asm volatile("st.async.weak.shared::cluster.mbarrier::complete_tx::bytes.v2.f32 [%0], {%1,%2}, [%3];"
                 ::"r"(addr), "f"(a), "f"(b), "r"(bar) : "memory");
}
__device__ __forceinline__ void st_async1(uint32_t addr, uint32_t v, uint32_t bar) {
    asm volatile("st.async.weak.shared::cluster.mbarrier::complete_tx::bytes.b32 [%0], %1, [%2];"
                 ::"r"(addr), "r"(v), "r"(bar) : "memory");
}
__device__ __forceinline__ void st_msg(uint4* p, float a, float b, uint32_t tag) {
    asm volatile("{\n.reg .b128 t;\n.reg .b64 lo, hi;\nmov.b64 lo, {%1,%2};\nmov.b64 hi, {%3,%3};\nmov.b128 t, {lo,hi};\n"
                 "st.relaxed.gpu.global.b128 [%0], t;\n}"
                 ::"l"(p), "r"(__float_as_uint(a)), "r"(__float_as_uint(b)), "r"(tag) : "memory");
}
__device__ __forceinline__ uint4 ld_msg(const uint4* p) {
    uint4 v;
    asm volatile("{\n.reg .b128 t;\n.reg .b64 lo, hi;\nld.relaxed.gpu.global.b128 t, [%4];\nmov.b128 {lo,hi}, t;\n"
                 "mov.b64 {%0,%1}, lo;\nmov.b64 {%2,%3}, hi;\n}"
                 : "=r"(v.x), "=r"(v.y), "=r"(v.z), "=r"(v.w) : "l"(p) : "memory");
    return v;
}
template <int N>
__device__ __forceinline__ float2 gather_msgs(const uint4* p, int stride, uint32_t tag) {
    uint4 v[N];
#pragma unroll
    for (int i = 0; i < N; i++) v[i] = ld_msg(p + i * stride);
    for (int n = 0;; n++) {
        bool ok = true;
#pragma unroll
        for (int i = 0; i < N; i++) ok = ok && (v[i].w == tag);
        if (__all_sync(0xffffffffu, ok)) break;
#pragma unroll
        for (int i = 0; i < N; i++) if (v[i].w != tag) v[i] = ld_msg(p + i * stride);
        if (n > (1 << 21)) __trap();
    }
    float a = __uint_as_float(v[0].x), b = __uint_as_float(v[0].y);
#pragma unroll
    for (int i = 1; i < N; i++) { a += __uint_as_float(v[i].x); b += __uint_as_float(v[i].y); }
    a += __shfl_xor_sync(0xffffffffu, a, 8);
    b += __shfl_xor_sync(0xffffffffu, b, 8);
    a += __shfl_xor_sync(0xffffffffu, a, 16);
    b += __shfl_xor_sync(0xffffffffu, b, 16);
    return make_float2(a, b);
}
__device__ __forceinline__ float2 gather_heads(const uint4* p, int own, float2 mine, uint32_t tag, int lane) {
    uint4 v[4];
    const int lg = lane >> 3;
#pragma unroll
    for (int i = 0; i < 4; i++) {
        if (lg + 4 * i == own) v[i] = make_uint4(__float_as_uint(mine.x), __float_as_uint(mine.y), tag, tag);
        else v[i] = ld_msg(p + i * 32);
    }
    for (int n = 0;; n++) {
        bool ok = true;
#pragma unroll
        for (int i = 0; i < 4; i++) ok = ok && (v[i].w == tag);
        if (__all_sync(0xffffffffu, ok)) break;
#pragma unroll
        for (int i = 0; i < 4; i++) if (v[i].w != tag) v[i] = ld_msg(p + i * 32);
        if (n > (1 << 21)) __trap();
    }
    float a = (__uint_as_float(v[0].x) + __uint_as_float(v[1].x)) + (__uint_as_float(v[2].x) + __uint_as_float(v[3].x));
    float b = (__uint_as_float(v[0].y) + __uint_as_float(v[1].y)) + (__uint_as_float(v[2].y) + __uint_as_float(v[3].y));
    a += __shfl_xor_sync(0xffffffffu, a, 8);
    b += __shfl_xor_sync(0xffffffffu, b, 8);
    a += __shfl_xor_sync(0xffffffffu, a, 16);
    b += __shfl_xor_sync(0xffffffffu, b, 16);
    return make_float2(a, b);
}
__device__ __forceinline__ void gather_msgs2(const uint4* p, const uint4* q, uint32_t tag, float2& u, float2& w) {
    uint4 v[4];
    v[0] = ld_msg(p); v[1] = ld_msg(p + 32); v[2] = ld_msg(q); v[3] = ld_msg(q + 32);
    for (int n = 0;; n++) {
        const bool ok = v[0].w == tag && v[1].w == tag && v[2].w == tag && v[3].w == tag;
        if (__all_sync(0xffffffffu, ok)) break;
        if (v[0].w != tag) v[0] = ld_msg(p);
        if (v[1].w != tag) v[1] = ld_msg(p + 32);
        if (v[2].w != tag) v[2] = ld_msg(q);
        if (v[3].w != tag) v[3] = ld_msg(q + 32);
        if (n > (1 << 21)) __trap();
    }
    float a = __uint_as_float(v[0].x) + __uint_as_float(v[1].x), b = __uint_as_float(v[0].y) + __uint_as_float(v[1].y);
    float c = __uint_as_float(v[2].x) + __uint_as_float(v[3].x), d = __uint_as_float(v[2].y) + __uint_as_float(v[3].y);
#pragma unroll
    for (int o = 8; o <= 16; o <<= 1) {
        a += __shfl_xor_sync(0xffffffffu, a, o); b += __shfl_xor_sync(0xffffffffu, b, o);
        c += __shfl_xor_sync(0xffffffffu, c, o); d += __shfl_xor_sync(0xffffffffu, d, o);
    }
    u = make_float2(a, b);
    w = make_float2(c, d);
}
__device__ __forceinline__ void ldsm4(uint32_t (&a)[4], uint32_t addr) {
    asm volatile("ldmatrix.sync.aligned.m8n8.x4.shared.b16 {%0,%1,%2,%3}, [%4];"
                 : "=r"(a[0]), "=r"(a[1]), "=r"(a[2]), "=r"(a[3]) : "r"(addr) : "memory");
}
__device__ __forceinline__ void ldsm4t(uint32_t (&a)[4], uint32_t addr) {
    asm volatile("ldmatrix.sync.aligned.m8n8.x4.trans.shared.b16 {%0,%1,%2,%3}, [%4];"
                 : "=r"(a[0]), "=r"(a[1]), "=r"(a[2]), "=r"(a[3]) : "r"(addr) : "memory");
}
__device__ __forceinline__ void ldsm2t(uint32_t (&a)[2], uint32_t addr) {
    asm volatile("ldmatrix.sync.aligned.m8n8.x2.trans.shared.b16 {%0,%1}, [%2];"
                 : "=r"(a[0]), "=r"(a[1]) : "r"(addr) : "memory");
}
__device__ __forceinline__ void mma16(float (&c)[4], const uint32_t (&a)[4], uint32_t b0, uint32_t b1) {
    asm volatile("mma.sync.aligned.m16n8k16.row.col.f32.bf16.bf16.f32 {%0,%1,%2,%3}, {%4,%5,%6,%7}, {%8,%9}, {%0,%1,%2,%3};"
                 : "+f"(c[0]), "+f"(c[1]), "+f"(c[2]), "+f"(c[3])
                 : "r"(a[0]), "r"(a[1]), "r"(a[2]), "r"(a[3]), "r"(b0), "r"(b1));
}
__device__ __forceinline__ void mma8(float (&c)[4], const uint32_t (&a)[2], uint32_t b0) {
    asm volatile("mma.sync.aligned.m16n8k8.row.col.f32.bf16.bf16.f32 {%0,%1,%2,%3}, {%4,%5}, {%6}, {%0,%1,%2,%3};"
                 : "+f"(c[0]), "+f"(c[1]), "+f"(c[2]), "+f"(c[3]) : "r"(a[0]), "r"(a[1]), "r"(b0));
}
__device__ __forceinline__ uint32_t lds32(uint32_t a) { uint32_t v; asm volatile("ld.shared.b32 %0, [%1];" : "=r"(v) : "r"(a) : "memory"); return v; }
__device__ __forceinline__ uint2 lds64(uint32_t a) { uint2 v; asm volatile("ld.shared.v2.b32 {%0,%1}, [%2];" : "=r"(v.x), "=r"(v.y) : "r"(a) : "memory"); return v; }
__device__ __forceinline__ float ldsf(uint32_t a) { float v; asm volatile("ld.shared.f32 %0, [%1];" : "=f"(v) : "r"(a) : "memory"); return v; }
__device__ __forceinline__ float2 ldsf2(uint32_t a) { float2 v; asm volatile("ld.shared.v2.f32 {%0,%1}, [%2];" : "=f"(v.x), "=f"(v.y) : "r"(a) : "memory"); return v; }
__device__ __forceinline__ float4 ldsf4(uint32_t a) { float4 v; asm volatile("ld.shared.v4.f32 {%0,%1,%2,%3}, [%4];" : "=f"(v.x), "=f"(v.y), "=f"(v.z), "=f"(v.w) : "r"(a) : "memory"); return v; }
__device__ __forceinline__ void stsf(uint32_t a, float v) { asm volatile("st.shared.f32 [%0], %1;" ::"r"(a), "f"(v) : "memory"); }
__device__ __forceinline__ void stsf2(uint32_t a, float x, float y) { asm volatile("st.shared.v2.f32 [%0], {%1,%2};" ::"r"(a), "f"(x), "f"(y) : "memory"); }
__device__ __forceinline__ void sts32(uint32_t a, uint32_t v) { asm volatile("st.shared.b32 [%0], %1;" ::"r"(a), "r"(v) : "memory"); }
__device__ __forceinline__ uint32_t pack_bf16(float hi, float lo) {
    uint32_t r;
    asm("cvt.rn.bf16x2.f32 %0, %1, %2;" : "=r"(r) : "f"(hi), "f"(lo));
    return r;
}
__device__ __forceinline__ void sts_bf16(uint32_t a, float v) {
    asm volatile("st.shared.b16 [%0], %1;" ::"r"(a), "h"((unsigned short)pack_bf16(0.f, v)) : "memory");
}
__device__ __forceinline__ float bf16r(float x) { return __uint_as_float(pack_bf16(x, 0.f)); }
__device__ __forceinline__ float silu_bf16(float x) { return bf16r(__fdividef(x, 1.0f + __expf(-x))); }

template <int PITCH>
__device__ __forceinline__ uint32_t gemv_addr(uint32_t tile, int col0, int lane) {
    return tile + ((lane & 7) + 8 * (lane >> 4)) * PITCH + (col0 + 8 * ((lane >> 3) & 1)) * 2;
}
template <int PITCH, int NK>
__device__ __forceinline__ void gemv_tile(float (&acc0)[4], float (&acc1)[4], uint32_t a_addr, uint32_t v_addr) {
#pragma unroll
    for (int ks = 0; ks < NK; ks++) {
        uint32_t a[4];
        ldsm4t(a, a_addr + ks * 16 * PITCH);
        const uint32_t b0 = lds32(v_addr + ks * 32), b1 = lds32(v_addr + ks * 32 + 16);
        if (ks & 1) mma16(acc1, a, b0, b1); else mma16(acc0, a, b0, b1);
    }
}

__device__ __forceinline__ float2 ln_stats(const float (&x)[18], float shift) {
    float s1 = 0.f, s2 = 0.f, t1 = 0.f, t2 = 0.f, u1 = 0.f, u2 = 0.f;
#pragma unroll
    for (int i = 0; i < 18; i += 3) {
        const float d = x[i] - shift, e = x[i + 1] - shift, f = x[i + 2] - shift;
        s1 += d; s2 = fmaf(d, d, s2);
        t1 += e; t2 = fmaf(e, e, t2);
        u1 += f; u2 = fmaf(f, f, u2);
    }
    s1 += t1 + u1;
    s2 += t2 + u2;
#pragma unroll
    for (int o = 16; o; o >>= 1) { s1 += __shfl_xor_sync(0xffffffffu, s1, o); s2 += __shfl_xor_sync(0xffffffffu, s2, o); }
    const float md = s1 * (1.0f / D);
    const float var = fmaxf(s2 * (1.0f / D) - md * md, 0.f);
    const float mean = bf16r(shift + md);
    float sd, inv;
    asm("sqrt.approx.f32 %0, %1;" : "=f"(sd) : "f"(bf16r(bf16r(var) + 1e-5f)));
    asm("rcp.approx.f32 %0, %1;" : "=f"(inv) : "f"(bf16r(sd)));
    return make_float2(mean, inv);
}
__device__ __forceinline__ float ln_norm(float x, float2 st) { return bf16r(bf16r(x - st.x) * st.y); }
__device__ __forceinline__ float modulate(float xn, float g1p, float shift) { return bf16r(bf16r(xn * g1p) + shift); }

template <int LO, int HI>
__device__ __forceinline__ void init_barriers(uint32_t bars) {
#pragma unroll
    for (int i = LO; i < HI; i++)
        mbar_init(bars + i * 8, i < B_EMPTY ? 1 : i < B_EMPTY + MAXT ? 4 : i < B_AFREE ? 8 : i == B_AFREE ? 8 : i == B_MODFREE ? 10 : i == B_WOFREE ? 6 : 1);
}

struct Maps { CUtensorMap mod, wq, k, v, wo, w1, w2, gb; };

__global__ void __launch_bounds__(NTHREADS, 1)
adaln_decode_kernel(const __grid_constant__ Maps maps, const __nv_bfloat16* __restrict__ gx,
                    const __nv_bfloat16* __restrict__ gc, __nv_bfloat16* __restrict__ gout) {
    extern __shared__ __align__(1024) unsigned char smem_raw[];
    const uint32_t sm = (uint32_t)__cvta_generic_to_shared(smem_raw);
    const uint32_t bars = sm + O_BAR;
    const int tid = threadIdx.x, warp = tid >> 5, lane = tid & 31;
    uint32_t j;
    asm("mov.u32 %0, %%cluster_ctarank;" : "=r"(j));
    uint32_t hu;
    asm("mov.u32 %0, %%clusterid.x;" : "=r"(hu));
    const int h = (int)hu;
    const int nt = j < 4 ? 11 : 10;
#define BAR(i) (bars + (i) * 8)

    if (__builtin_expect(warp == NCW, 1)) {
        uint64_t pol;
        asm volatile("createpolicy.fractional.L2::evict_first.b64 %0, 1.0;" : "=l"(pol));
        const uint32_t tstart = __shfl_sync(0xffffffffu, gtime32(), 0);
        if (lane == 0) {
            init_barriers<B_MODA, B_K>(bars);
            asm volatile("fence.mbarrier_init.release.cluster;" ::: "memory");
            mbar_expect_tx(BAR(B_MODA), SZ_MOD);
            tma2d(sm + O_MODA, &maps.mod, (h & 1) * D + 96 * j, (h >> 1) * 72, BAR(B_MODA), pol);
            mbar_expect_tx(BAR(B_WQ), SZ_WQ);
            tma3d(sm + O_WQ, &maps.wq, 0, 96 * j, h * 4, BAR(B_WQ), pol);
        }
        __syncwarp();
        bar_arrive(0, NCT + 32);
        asm volatile("barrier.cluster.arrive.relaxed.aligned;" ::: "memory");
        bar_sync(3, 128);
        if (lane != 0) return;
        uint32_t q0 = 0, q1 = 0, q2 = BAR(B_MODA), q3 = BAR(B_WQ);
        static_assert(DEPTH == 4, "window registers");
        uint32_t due = tstart + (D * 2 * D * 2 + D * 4096 * 2 / 3) / PACE_A + (STAGGER * (2 * h - 15)) / 2;
        bool soft_on = false;
#define PACE(bytes_all, rate, softbar) { \
            uint32_t now_ = gtime32(); \
            while ((int)(now_ - due) < 0) now_ = gtime32(); \
            if (SOFT > 0 && soft_on && (softbar) && !mbar_test(softbar)) { \
                const uint32_t lim_ = now_ + SOFT; \
                do { now_ = gtime32(); } while (!mbar_test(softbar) && (int)(now_ - lim_) < 0); \
                due = now_; \
            } \
            due += (uint32_t)((bytes_all) / (rate)); }
#define STAGE_BEGIN(bar_, bytes_all, rate) \
        { if (q0) mbar_spin(q0); q0 = q1; q1 = q2; q2 = q3; q3 = (bar_); PACE(bytes_all, rate, q0); }
        const int cb = h * CS + j;
#pragma unroll 1
        for (int i = 1; i < 3; i++) {
            const uint32_t b = BAR(B_WQ + i);
            STAGE_BEGIN(b, D * 4096 * 2 / 3, PACE_A);
            mbar_expect_tx(b, SZ_WQ);
            tma3d(sm + O_WQ + i * SZ_WQ, &maps.wq, 0, 96 * j + i * 32, h * 4, b, pol);
        }
#pragma unroll 1
        for (int i = 0; i < 2; i++) {
            const uint32_t b = BAR(B_MODB + i);
            const bool real = (h & 3) != 3;
            if (real) {
                STAGE_BEGIN(b, D * 3 * D * 2 / 2, PACE_A);
                mbar_expect_tx(b, SZ_MOD);
                tma2d(sm + O_MODB + i * SZ_MOD, &maps.mod, (2 + (h & 3)) * D + 96 * j, (h >> 2) * 144 + i * 72, b, pol);
            } else {
                PACE(D * 3 * D * 2 / 2, PACE_A, 0u);
            }
        }
        {
            const int row0 = h * SK + (SK - WINDOW);
            int slot = 0;
#pragma unroll 1
            for (int n = 0; n < 2 * nt; n++) {
                const bool isv = n >= nt;
                const int t = isv ? n - nt : n;
                const uint32_t b = BAR((isv ? B_V : B_K) + t), dst = sm + slot_off(slot);
                const CUtensorMap* m = isv ? &maps.v : &maps.k;
                soft_on = n >= SOFT_FROM;
                STAGE_BEGIN(b, (nt == 11 ? NKV * WINDOW * DH * 4 / 22 : NKV * WINDOW * DH * 4 / 20), PACE_GBPS);
                const int gt = CS * t + j;
                if (n == NRING) mbar_spin(BAR(B_MODFREE));
                if (n >= NSLOT) { const int pn = n - NSLOT; mbar_spin(BAR(B_EMPTY + (pn < nt ? pn : MAXT + pn - nt))); }
                mbar_expect_tx(b, SZ_KV);
                tma3d(dst, m, 0, row0 + gt * 64, 0, b, pol);
                slot = slot == NSLOT - 1 ? 0 : slot + 1;
            }
        }
#pragma unroll 1
        for (int i = 0; i < 4; i++) {
            const uint32_t b = BAR(B_WO + i);
            STAGE_BEGIN(b, D * 4096 * 2 / 4, PACE_WO);
            if (i == 0) { mbar_spin(BAR(B_AFREE)); mbar_spin(BAR(B_MODFREE)); }
            mbar_expect_tx(b, SZ_WO);
            tma2d(sm + O_WO + i * SZ_WO, &maps.wo, 96 * j, h * 256 + i * 64, b, pol);
        }
#pragma unroll 1
        for (int i = 0; i < 4; i++) {
            const uint32_t b = BAR(B_W1 + i);
            STAGE_BEGIN(b, D * FF * 2 / 4, (i < 2 ? PACE_W1 : PACE_W1B));
            if (i == 0) {
                mbar_spin(BAR(B_EMPTY + MAXT + 14 - nt));
                mbar_spin(BAR(B_EMPTY + MAXT + 15 - nt));
            }
            if (i == 2) mbar_spin(BAR(B_EMPTY + MAXT + nt - 1));
            mbar_expect_tx(b, SZ_W1);
            tma2d(sm + (i < 2 ? O_W1A + i * SZ_W1 : O_W1B + (i - 2) * SZ_W1), &maps.w1, cb * 48, i * 144, b, pol);
        }
#pragma unroll 1
        for (int i = 0; i < 3; i++) {
            const uint32_t b = BAR(B_W2 + i);
            STAGE_BEGIN(b, D * FF * 2 / 3, PACE_W2);
            mbar_expect_tx(b, SZ_W2);
            tma2d(sm + O_W2 + i * SZ_W2, &maps.w2, 96 * j, h * 288 + i * 96, b, pol);
        }
        if (h < 6) {
            mbar_spin(BAR(B_WOFREE));
            mbar_expect_tx(BAR(B_GBT), SZ_GBT);
#pragma unroll 1
            for (int i = 0; i < 3; i++)
                tma2d(sm + O_GBT + i * 192 * P_GB, &maps.gb, 5 * D + 96 * j + 16 * h, i * 192, BAR(B_GBT), pol);
        }
#undef STAGE_BEGIN
#undef PACE
        asm volatile("barrier.cluster.wait;" ::: "memory");
        return;
    }

    const int g = lane >> 2, t4 = lane & 3;
    const int r7 = lane & 7, lg = lane >> 3;
    uint4* const a1_out = g_scr.a1 + ((((h & 1) * 6 + j) * 6) * 8 + (h >> 1)) * 8;
    uint4* const a2_out = g_scr.a2 + ((((h & 3) * 6 + j) * 6) * 4 + (h >> 2)) * 8;
    uint4* const c1_out = g_scr.c1 + ((j * 6) * 16 + h) * 8;
    uint4* const d1_out = g_scr.d1 + ((j * 6) * 16 + h) * 8;

    uint32_t xv = 0, cv = 0;
    if (warp >= 9) {
        if (lane == 0) {
            if (warp == 9) init_barriers<B_K, B_EMPTY>(bars);
            else if (warp == 10) init_barriers<B_EMPTY, B_AFREE>(bars);
            else {
                init_barriers<B_AFREE, NBAR>(bars);
                mbar_expect_tx(BAR(B_XQ), CS * 1024);
                mbar_expect_tx(BAR(B_XB), CS * 1040);
                mbar_expect_tx(BAR(B_XC), CS * 192);
                mbar_expect_tx(BAR(B_XG), CS * 768);
                mbar_expect_tx(BAR(B_XD), CS * 96);
            }
            asm volatile("fence.mbarrier_init.release.cluster;" ::: "memory");
        }
        __syncwarp();
        bar_arrive(3, 128);
    } else {
        xv = __ldg(reinterpret_cast<const uint32_t*>(gx) + tid);
        cv = __ldg(reinterpret_cast<const uint32_t*>(gc) + tid);
    }
    uint32_t xall[9];
    uint32_t xc0 = 0, xc1 = 0;
    if (warp < 6) {
#pragma unroll
        for (int i = 0; i < 9; i++) xall[i] = __ldg(reinterpret_cast<const uint32_t*>(gx) + lane + 32 * i);
        xc0 = __ldg(reinterpret_cast<const unsigned short*>(gx) + 96 * j + warp * 16 + r7);
        xc1 = __ldg(reinterpret_cast<const unsigned short*>(gx) + 96 * j + warp * 16 + r7 + 8);
    }
    asm volatile("barrier.cluster.arrive.relaxed.aligned;" ::: "memory");
    uint32_t epoch = 0;
    if (tid == 288) epoch = *(volatile unsigned*)&g_scr.epoch;
    if (t4 == 0) {
        if (warp < 6) st_msg(a1_out + warp * 64 + g, 0.f, 0.f, 0);
        else if (warp >= 8) {
            st_msg(a2_out + (warp - 8) * 32 + g, 0.f, 0.f, 0);
            if (warp < 10) st_msg(a2_out + (warp - 4) * 32 + g, 0.f, 0.f, 0);
        }
    }
    if (tid < 288) {
        stsf2(sm + O_XS + tid * 8, __uint_as_float(xv << 16), __uint_as_float(xv & 0xffff0000u));
        const float c0 = silu_bf16(__uint_as_float(cv << 16)), c1 = silu_bf16(__uint_as_float(cv & 0xffff0000u));
        sts32(sm + O_SC + tid * 4, (__float_as_uint(c0) >> 16) | (__float_as_uint(c1) & 0xffff0000u));
    }
    if (tid == 288) sts32(sm + O_TAG, epoch + 1);
    float xn0 = 0.f, xn1 = 0.f;
    if (warp < 6) {
        float xr[18];
#pragma unroll
        for (int i = 0; i < 9; i++) { xr[2 * i] = __uint_as_float(xall[i] << 16); xr[2 * i + 1] = __uint_as_float(xall[i] & 0xffff0000u); }
        const float2 st = ln_stats(xr, __shfl_sync(0xffffffffu, xr[0], 0));
        xn0 = ln_norm(__uint_as_float(xc0 << 16), st);
        xn1 = ln_norm(__uint_as_float(xc1 << 16), st);
    }
    bar_sync(0, NCT + 32);
    const uint32_t tag = lds32(sm + O_TAG);
    if (tid == 6 * 32) {
        asm volatile("prefetch.tensormap [%0];" ::"l"(&maps.k) : "memory");
        asm volatile("prefetch.tensormap [%0];" ::"l"(&maps.v) : "memory");
    }
    if (tid == 7 * 32) {
        asm volatile("prefetch.tensormap [%0];" ::"l"(&maps.wo) : "memory");
        asm volatile("prefetch.tensormap [%0];" ::"l"(&maps.w1) : "memory");
        asm volatile("prefetch.tensormap [%0];" ::"l"(&maps.w2) : "memory");
    }
    if (warp < 6) {
        float acc0[4] = {0.f, 0.f, 0.f, 0.f}, acc1[4] = {0.f, 0.f, 0.f, 0.f};
        const uint32_t va = sm + O_SC + ((h >> 1) * 72 + 2 * t4) * 2;
        mbar_wait(BAR(B_MODA));
        gemv_tile<P_MOD, 4>(acc0, acc1, gemv_addr<P_MOD>(sm + O_MODA, warp * 16, lane), va);
        {
            uint32_t a[2];
            ldsm2t(a, sm + O_MODA + (64 + r7) * P_MOD + (warp * 16 + 8 * (lg & 1)) * 2);
            mma8(acc0, a, lds32(va + 128));
        }
        if (t4 == 0) st_msg(a1_out + warp * 64 + g, acc0[0] + acc1[0], acc0[2] + acc1[2], tag);
        if (lane == 0) mbar_arrive(BAR(B_MODFREE));
        const uint4* in = g_scr.a1 + (j * 6 + warp) * 64 + lane;
        float2 sa, ca;
        gather_msgs2(in, in + 36 * 64, tag, sa, ca);
        if (lg == 0) {
            const int c = warp * 16 + r7;
            sts_bf16(sm + O_HV + c * 2, modulate(xn0, bf16r(1.f + bf16r(ca.x)), bf16r(sa.x)));
            sts_bf16(sm + O_HV + (c + 8) * 2, modulate(xn1, bf16r(1.f + bf16r(ca.y)), bf16r(sa.y)));
        }
    }
    asm volatile("barrier.cluster.wait.aligned;" ::: "memory");
    if (warp < 8) {
        bar_sync(1, 256);
        float a00[4] = {0.f, 0.f, 0.f, 0.f}, a01[4] = {0.f, 0.f, 0.f, 0.f};
        float a10[4] = {0.f, 0.f, 0.f, 0.f}, a11[4] = {0.f, 0.f, 0.f, 0.f};
        const uint32_t va = sm + O_HV + 4 * t4;
        const uint32_t a_off = (warp >> 1) * 4096 + (r7 + 8 * (lg >> 1)) * 128 + (((4 * (warp & 1) + (lg & 1)) ^ r7) << 4);
#pragma unroll
        for (int i = 0; i < 3; i++) {
            mbar_wait(BAR(B_WQ + i));
#pragma unroll
            for (int k2 = 0; k2 < 2; k2++) {
                const int ks = 2 * i + k2;
                const uint32_t b0 = lds32(va + ks * 32), b1 = lds32(va + ks * 32 + 16);
                uint32_t a[4];
                ldsm4t(a, sm + O_WQ + i * SZ_WQ + k2 * 2048 + a_off);
                if (k2) mma16(a01, a, b0, b1); else mma16(a00, a, b0, b1);
                ldsm4t(a, sm + O_WQ + i * SZ_WQ + k2 * 2048 + (a_off ^ 32));
                if (k2) mma16(a11, a, b0, b1); else mma16(a10, a, b0, b1);
            }
        }
        const uint32_t dst = sm + O_QBUF + j * 1024 + (warp * 8 + g) * 16;
        const float v0 = a00[0] + a01[0], v1 = a00[2] + a01[2], v2 = a10[0] + a11[0], v3 = a10[2] + a11[2];
        st_async4(mapa(dst, t4), v0, v1, v2, v3, mapa(BAR(B_XQ), t4));
        if (t4 < 2) st_async4(mapa(dst, t4 + 4), v0, v1, v2, v3, mapa(BAR(B_XQ), t4 + 4));
        if (lane == 0) mbar_arrive(BAR(B_AFREE));
        mbar_wait_cluster(BAR(B_XQ));
        float q = 0.f;
#pragma unroll
        for (int s = 0; s < CS; s++) q += ldsf(sm + O_QBUF + s * 1024 + tid * 4);
        const int e = tid & 3;
        const int n = warp * 32 + (e >> 1) * 16 + g + 8 * (e & 1);
        sts_bf16(sm + O_QV + n * 2, q);
    }
    if (warp >= 8) {
        if ((h & 3) != 3) {
            mbar_wait(BAR(B_MODB));
            mbar_wait(BAR(B_MODB + 1));
            const uint32_t va = sm + O_SC + ((h >> 2) * 144 + 2 * t4) * 2;
            for (int l = warp - 8; l < 6; l += 4) {
                float acc0[4] = {0.f, 0.f, 0.f, 0.f}, acc1[4] = {0.f, 0.f, 0.f, 0.f};
                gemv_tile<P_MOD, 9>(acc0, acc1, gemv_addr<P_MOD>(sm + O_MODB, l * 16, lane), va);
                if (t4 == 0) st_msg(a2_out + l * 32 + g, acc0[0] + acc1[0], acc0[2] + acc1[2], tag);
            }
            __syncwarp();
        }
        if (lane == 0) mbar_arrive(BAR(B_MODFREE));
    }

    bar_sync(2, NCT);
    uint32_t qb[16];
#pragma unroll
    for (int ks = 0; ks < 8; ks++) {
        const uint32_t a = sm + O_QV + ((g & 1) * 128 + ks * 16 + 2 * t4) * 2;
        qb[2 * ks] = lds32(a);
        qb[2 * ks + 1] = lds32(a + 16);
    }
    float sc[4];
    {
        const int grp = warp >> 2, mi = lg;
        const uint32_t a_off = (16 * (warp & 3) + r7 + 8 * (mi & 1)) * 128 + (((mi >> 1) ^ r7) << 4);
        float mx = -INFINITY;
#pragma unroll
        for (int it = 0; it < 4; it++) {
            const int t = grp + 3 * it;
            sc[it] = -INFINITY;
            if (t < nt) {
                mbar_wait(BAR(B_K + t));
                const uint32_t base = sm + slot_off(t % NSLOT);
                float c0[4] = {0.f, 0.f, 0.f, 0.f}, c1[4] = {0.f, 0.f, 0.f, 0.f};
#pragma unroll
                for (int ks = 0; ks < 8; ks++) {
                    uint32_t a[4];
                    ldsm4(a, base + (ks >> 2) * 8192 + (a_off ^ ((ks & 3) << 5)));
                    if (ks & 1) mma16(c1, a, qb[2 * ks], qb[2 * ks + 1]); else mma16(c0, a, qb[2 * ks], qb[2 * ks + 1]);
                }
                __syncwarp();
                if (lane == 0) mbar_arrive(BAR(B_EMPTY + t));
                const float v = t4 == 0 ? c0[0] + c1[0] : t4 == 1 ? c0[1] + c1[1] : t4 == 2 ? c0[2] + c1[2] : c0[3] + c1[3];
                sc[it] = bf16r(bf16r(v) * 0.08838834764831845f);
                mx = fmaxf(mx, sc[it]);
            }
        }
        mx = fmaxf(mx, __shfl_xor_sync(0xffffffffu, mx, 2));
        mx = fmaxf(mx, __shfl_xor_sync(0xffffffffu, mx, 4));
        mx = fmaxf(mx, __shfl_xor_sync(0xffffffffu, mx, 8));
        mx = fmaxf(mx, __shfl_xor_sync(0xffffffffu, mx, 16));
        if (lane < 2) stsf(sm + O_WMAX + (warp * 2 + lane) * 4, mx);
    }
    bar_sync(2, NCT);
    float cta_max;
    {
        const int hd = t4 & 1, grp = warp >> 2;
        float m = -INFINITY;
#pragma unroll
        for (int w = 0; w < NCW; w++) m = fmaxf(m, ldsf(sm + O_WMAX + (w * 2 + hd) * 4));
        cta_max = m;
        float l = 0.f;
#pragma unroll
        for (int it = 0; it < 4; it++) {
            const int t = grp + 3 * it;
            if (t < nt) {
                const float p = __expf(sc[it] - m);
                l += p;
                sts_bf16(sm + O_PV + (hd * PV_PITCH + t * 64 + 16 * (warp & 3) + g + 8 * (t4 >> 1)) * 2, p);
            }
        }
        l += __shfl_xor_sync(0xffffffffu, l, 2);
        l += __shfl_xor_sync(0xffffffffu, l, 4);
        l += __shfl_xor_sync(0xffffffffu, l, 8);
        l += __shfl_xor_sync(0xffffffffu, l, 16);
        if (lane < 2) stsf(sm + O_WL + (warp * 2 + lane) * 4, l);
    }
    if (warp < 6 && t4 == 0) {
        st_msg(c1_out + warp * 128 + g, 0.f, 0.f, 0);
        st_msg(d1_out + warp * 128 + g, 0.f, 0.f, 0);
    }
    bar_sync(2, NCT);

    if (warp >= 8) {
        const int m = warp - 8;
        if (m < 3) {
#pragma unroll 1
            for (int l = 0; l < 6; l++) {
                const float2 v = gather_msgs<1>(g_scr.a2 + ((m * 6 + j) * 6 + l) * 32 + lane, 0, tag);
                float a = bf16r(v.x), b = bf16r(v.y);
                if (m == 0) {
                    if (lg == 0) stsf2(sm + O_GA + (l * 8 + r7) * 8, a, b);
                } else {
                    if (m == 2) { a = bf16r(1.f + a); b = bf16r(1.f + b); }
                    const uint32_t dst = sm + (m == 1 ? O_SB : O_G1P) + ((j * 6 + l) * 8 + r7) * 8;
                    st_async2(mapa(dst, lg), a, b, mapa(BAR(B_XG), lg));
                    if (lg < 2) st_async2(mapa(dst, lg + 4), a, b, mapa(BAR(B_XG), lg + 4));
                }
            }
            __syncwarp();
            if (lane == 0 && m == 0) mbar_arrive(BAR(B_GATES));
        }
        if (warp == 8) {
            const float m0 = __shfl_sync(0xffffffffu, cta_max, 0), m1 = __shfl_sync(0xffffffffu, cta_max, 1);
            float l0 = 0.f, l1 = 0.f;
#pragma unroll
            for (int w = 0; w < NCW; w++) { const float2 v = ldsf2(sm + O_WL + w * 8); l0 += v.x; l1 += v.y; }
            if (lane < CS) st_async4(mapa(sm + O_MLBUF + j * 16, lane), m0, m1, l0, l1, mapa(BAR(B_XB), lane));
        }
    } else {
        const int mi = lg;
        const uint32_t a_off = (warp >> 2) * 8192 + (r7 + 8 * (mi >> 1)) * 128 + (((2 * (warp & 3) + (mi & 1)) ^ r7) << 4);
        const uint32_t pa = sm + O_PV + ((g & 1) * PV_PITCH + 2 * t4) * 2;
        float c0[4] = {0.f, 0.f, 0.f, 0.f}, c1[4] = {0.f, 0.f, 0.f, 0.f};
#pragma unroll 1
        for (int t = 0; t < nt; t++) {
            uint32_t b[8];
#pragma unroll
            for (int ks = 0; ks < 4; ks++) { b[2 * ks] = lds32(pa + (t * 64 + ks * 16) * 2); b[2 * ks + 1] = lds32(pa + (t * 64 + ks * 16) * 2 + 16); }
            mbar_wait(BAR(B_V + t));
            const uint32_t base = sm + slot_off((nt + t) % NSLOT) + a_off;
#pragma unroll
            for (int ks = 0; ks < 4; ks++) {
                uint32_t a[4];
                ldsm4t(a, base + ks * 2048);
                if (ks & 1) mma16(c1, a, b[2 * ks], b[2 * ks + 1]); else mma16(c0, a, b[2 * ks], b[2 * ks + 1]);
            }
            __syncwarp();
            if (lane == 0) mbar_arrive(BAR(B_EMPTY + MAXT + t));
        }
        const uint32_t dst = sm + O_OBUF + j * 1024 + (warp * 8 + g) * 16;
        const float v0 = c0[0] + c1[0], v1 = c0[1] + c1[1], v2 = c0[2] + c1[2], v3 = c0[3] + c1[3];
        st_async4(mapa(dst, t4), v0, v1, v2, v3, mapa(BAR(B_XB), t4));
        if (t4 < 2) st_async4(mapa(dst, t4 + 4), v0, v1, v2, v3, mapa(BAR(B_XB), t4 + 4));
        mbar_wait_cluster(BAR(B_XB));
        {
            const int e = tid & 3, hd = e & 1;
            float ms[CS], ls[CS], M = -INFINITY;
#pragma unroll
            for (int s = 0; s < CS; s++) {
                const float4 v = ldsf4(sm + O_MLBUF + s * 16);
                ms[s] = hd ? v.y : v.x; ls[s] = hd ? v.w : v.z;
                M = fmaxf(M, ms[s]);
            }
            float L = 0.f, o = 0.f;
#pragma unroll
            for (int s = 0; s < CS; s++) {
                const float w = __expf(ms[s] - M);
                L = fmaf(w, ls[s], L);
                o = fmaf(w, ldsf(sm + O_OBUF + s * 1024 + tid * 4), o);
            }
            const int n = hd * 128 + warp * 16 + g + 8 * (e >> 1);
            sts_bf16(sm + O_OV + n * 2, o / L);
        }
        bar_sync(1, 256);
        if (warp < 6) {
            float acc0[4] = {0.f, 0.f, 0.f, 0.f}, acc1[4] = {0.f, 0.f, 0.f, 0.f};
            const uint32_t va = sm + O_OV + 4 * t4;
#pragma unroll
            for (int i = 0; i < 4; i++) {
                mbar_wait(BAR(B_WO + i));
                gemv_tile<P_WO, 4>(acc0, acc1, gemv_addr<P_WO>(sm + O_WO + i * SZ_WO, warp * 16, lane), va + i * 128);
            }
            const float p0 = acc0[0] + acc1[0], p1 = acc0[2] + acc1[2];
            if (t4 == 0) st_msg(c1_out + warp * 128 + g, p0, p1, tag);
            const float2 mine = make_float2(__shfl_sync(0xffffffffu, p0, 4 * r7), __shfl_sync(0xffffffffu, p1, 4 * r7));
            if (lane == 0) mbar_arrive(BAR(B_WOFREE));
            const int c = 96 * j + warp * 16 + r7;
            const float x0 = ldsf(sm + O_XS + c * 4), x1 = ldsf(sm + O_XS + (c + 8) * 4);
            mbar_wait(BAR(B_GATES));
            mbar_wait_cluster(BAR(B_XG));
            const float2 ga = ldsf2(sm + O_GA + (warp * 8 + r7) * 8);
            { const uint32_t t0 = gtime32(); while ((int)(gtime32() - t0) < C1_DELAY) {} }
            const float2 at = gather_heads(g_scr.c1 + (j * 6 + warp) * 128 + lane, h, mine, tag, lane);
            const float y0 = x0 + bf16r(ga.x * bf16r(at.x)), y1 = x1 + bf16r(ga.y * bf16r(at.y));
            const uint32_t xp = pack_bf16(y1, y0), dst2 = sm + O_X2 + ((j * 6 + warp) * 8 + r7) * 4;
            st_async1(mapa(dst2, lg), xp, mapa(BAR(B_XC), lg));
            if (lg < 2) st_async1(mapa(dst2, lg + 4), xp, mapa(BAR(B_XC), lg + 4));
        }
    }
    if (warp >= 6 && warp < 9) mbar_wait_cluster(BAR(B_XG));
    float2 g1 = make_float2(0.f, 0.f), sb = make_float2(0.f, 0.f);
    if (tid < 288) { g1 = ldsf2(sm + O_G1P + tid * 8); sb = ldsf2(sm + O_SB + tid * 8); }
    const int mt1 = warp % 3, kq = warp / 3;
    uint32_t wa[9][4];
    {
        const uint32_t a_addr = gemv_addr<P_W1>(sm + (kq < 2 ? O_W1A + kq * SZ_W1 : O_W1B + (kq - 2) * SZ_W1), mt1 * 16, lane);
        mbar_wait(BAR(B_W1 + kq));
#pragma unroll
        for (int ks = 0; ks < 9; ks++) ldsm4t(wa[ks], a_addr + ks * 16 * P_W1);
    }
    if (warp < 9) {
        mbar_wait_cluster(BAR(B_XC));
        uint32_t xp[9];
#pragma unroll
        for (int i = 0; i < 9; i++) xp[i] = lds32(sm + O_X2 + (lane + 32 * i) * 4);
        const uint32_t mine = lds32(sm + O_X2 + tid * 4);
        float xr[18];
#pragma unroll
        for (int i = 0; i < 9; i++) { xr[2 * i] = __uint_as_float(xp[i] << 16); xr[2 * i + 1] = __uint_as_float(xp[i] & 0xffff0000u); }
        const float2 st = ln_stats(xr, __shfl_sync(0xffffffffu, xr[0], 0));
        const float x0 = __uint_as_float(mine << 16), x1 = __uint_as_float(mine & 0xffff0000u);
        const int kk = tid & 7;
        const uint32_t dst = sm + O_H2 + ((tid >> 3) * 16 + (kk >> 1) * 4 + (kk & 1)) * 2;
        sts_bf16(dst, modulate(ln_norm(x0, st), g1.x, sb.x));
        sts_bf16(dst + 4, modulate(ln_norm(x1, st), g1.y, sb.y));
    }
    bar_sync(2, NCT);
    {
        float acc0[4] = {0.f, 0.f, 0.f, 0.f}, acc1[4] = {0.f, 0.f, 0.f, 0.f}, acc2[4] = {0.f, 0.f, 0.f, 0.f};
        const uint32_t va = sm + O_H2 + (kq * 144 + 4 * t4) * 2;
        uint2 bb[9];
#pragma unroll
        for (int ks = 0; ks < 9; ks++) bb[ks] = lds64(va + ks * 32);
#pragma unroll
        for (int ks = 0; ks < 9; ks += 3) {
            mma16(acc0, wa[ks], bb[ks].x, bb[ks].y);
            mma16(acc1, wa[ks + 1], bb[ks + 1].x, bb[ks + 1].y);
            mma16(acc2, wa[ks + 2], bb[ks + 2].x, bb[ks + 2].y);
        }
        if (t4 == 0) {
            stsf(sm + O_RED1 + (kq * 48 + mt1 * 16 + g) * 4, acc0[0] + acc1[0] + acc2[0]);
            stsf(sm + O_RED1 + (kq * 48 + mt1 * 16 + g + 8) * 4, acc0[2] + acc1[2] + acc2[2]);
        }
    }
    bar_sync(2, NCT);
    if (warp == 6) {
        const int pi = lane < 24 ? lane : 0;
        float2 s = ldsf2(sm + O_RED1 + pi * 8);
#pragma unroll
        for (int q = 1; q < 4; q++) { const float2 v = ldsf2(sm + O_RED1 + q * 192 + pi * 8); s.x += v.x; s.y += v.y; }
        const uint32_t pk = pack_bf16(silu_bf16(bf16r(s.y)), silu_bf16(bf16r(s.x)));
        const uint32_t dst = sm + O_H1 + j * 96 + ((pi >> 3) * 8 + (pi & 3) * 2 + ((pi >> 2) & 1)) * 4;
        if (lane < 24) {
#pragma unroll
            for (int d = 0; d < CS; d++) st_async1(mapa(dst, d), pk, mapa(BAR(B_XD), d));
        }
    }
    if (warp >= 6) {
        if (h < 6) {
            float acc0[4] = {0.f, 0.f, 0.f, 0.f}, acc1[4] = {0.f, 0.f, 0.f, 0.f};
            const int k = warp - 6;
            mbar_wait(BAR(B_GBT));
            gemv_tile<P_GB, 6>(acc0, acc1, gemv_addr<P_GB>(sm + O_GBT + k * 96 * P_GB, 0, lane), sm + O_SC + (k * 96 + 2 * t4) * 2);
            if (t4 == 0) {
                stsf(sm + O_GB + (k * 16 + g) * 4, acc0[0] + acc1[0]);
                stsf(sm + O_GB + (k * 16 + g + 8) * 4, acc0[2] + acc1[2]);
            }
            __syncwarp();
            bar_arrive(4, 7 * 32);
        }
    } else {
        const uint32_t a_addr = gemv_addr<P_W2>(sm + O_W2, warp * 16, lane);
        mbar_wait_cluster(BAR(B_XD));
        uint2 bb[18];
#pragma unroll
        for (int ks = 0; ks < 18; ks++) bb[ks] = lds64(sm + O_H1 + ks * 32 + t4 * 8);
        float acc[3][4];
#pragma unroll
        for (int i = 0; i < 3; i++) acc[i][0] = acc[i][1] = acc[i][2] = acc[i][3] = 0.f;
#pragma unroll
        for (int i = 0; i < 3; i++) {
            mbar_wait(BAR(B_W2 + i));
#pragma unroll
            for (int k = 0; k < 6; k++) {
                uint32_t a[4];
                ldsm4t(a, a_addr + (i * 6 + k) * 16 * P_W2);
                mma16(acc[k % 3], a, bb[i * 6 + k].x, bb[i * 6 + k].y);
            }
        }
        const float p0 = acc[0][0] + acc[1][0] + acc[2][0], p1 = acc[0][2] + acc[1][2] + acc[2][2];
        if (t4 == 0) st_msg(d1_out + warp * 128 + g, p0, p1, tag);
        if (warp == h) {
            const float2 mine = make_float2(__shfl_sync(0xffffffffu, p0, 4 * r7), __shfl_sync(0xffffffffu, p1, 4 * r7));
            const uint32_t xp = lds32(sm + O_X2 + ((j * 6 + warp) * 8 + r7) * 4);
            const float2 x2 = make_float2(__uint_as_float(xp << 16), __uint_as_float(xp & 0xffff0000u));
            bar_sync(4, 7 * 32);
            float gb0 = 0.f, gb1 = 0.f;
#pragma unroll
            for (int k = 0; k < 6; k++) { gb0 += ldsf(sm + O_GB + (k * 16 + r7) * 4); gb1 += ldsf(sm + O_GB + (k * 16 + r7 + 8) * 4); }
            gb0 = bf16r(gb0);
            gb1 = bf16r(gb1);
            const float2 y = gather_heads(g_scr.d1 + (j * 6 + warp) * 128 + lane, h, mine, tag, lane);
            if (lg == 0) {
                const int c = 96 * j + warp * 16 + r7;
                const uint32_t o2 = pack_bf16(x2.y + bf16r(gb1 * bf16r(y.y)), x2.x + bf16r(gb0 * bf16r(y.x)));
                gout[c] = __ushort_as_bfloat16((unsigned short)o2);
                gout[c + 8] = __ushort_as_bfloat16((unsigned short)(o2 >> 16));
            }
            if (blockIdx.x == 0 && lane == 0) *(volatile unsigned*)&g_scr.epoch = tag;
        }
    }
#undef BAR
}

typedef CUresult (*EncodeTiledFn)(CUtensorMap*, CUtensorMapDataType, cuuint32_t, void*, const cuuint64_t*,
                                  const cuuint64_t*, const cuuint32_t*, const cuuint32_t*, CUtensorMapInterleave,
                                  CUtensorMapSwizzle, CUtensorMapL2promotion, CUtensorMapFloatOOBfill);

void encode2d(EncodeTiledFn enc, CUtensorMap* m, const void* base, uint64_t rows, uint64_t cols, uint32_t box_cols,
              uint32_t box_rows, CUtensorMapSwizzle swz,
              CUtensorMapL2promotion promo = CU_TENSOR_MAP_L2_PROMOTION_NONE) {
    cuuint64_t dims[2] = {cols, rows};
    cuuint64_t strides[1] = {cols * 2};
    cuuint32_t box[2] = {box_cols, box_rows};
    cuuint32_t es[2] = {1, 1};
    enc(m, CU_TENSOR_MAP_DATA_TYPE_BFLOAT16, 2, const_cast<void*>(base), dims, strides, box, es,
        CU_TENSOR_MAP_INTERLEAVE_NONE, swz, promo, CU_TENSOR_MAP_FLOAT_OOB_FILL_NONE);
}

void encode3d(EncodeTiledFn enc, CUtensorMap* m, const void* base, uint64_t d0, uint64_t d1, uint64_t d2, uint64_t s1,
              uint64_t s2, uint32_t b0, uint32_t b1, uint32_t b2, CUtensorMapSwizzle swz) {
    cuuint64_t dims[3] = {d0, d1, d2};
    cuuint64_t strides[2] = {s1, s2};
    cuuint32_t box[3] = {b0, b1, b2};
    cuuint32_t es[3] = {1, 1, 1};
    enc(m, CU_TENSOR_MAP_DATA_TYPE_BFLOAT16, 3, const_cast<void*>(base), dims, strides, box, es,
        CU_TENSOR_MAP_INTERLEAVE_NONE, swz, CU_TENSOR_MAP_L2_PROMOTION_NONE, CU_TENSOR_MAP_FLOAT_OOB_FILL_NONE);
}

struct Fallback { float sc[D], mod[6 * D], x[D], h[D], q[4096], o[4096], y[D], x2[D], u[FF]; };
__device__ Fallback g_fb;

__global__ void fb_prepare(const __nv_bfloat16* x, const __nv_bfloat16* c) {
    const int i = threadIdx.x;
    g_fb.x[i] = __bfloat162float(x[i]);
    const float v = __bfloat162float(c[i]);
    g_fb.sc[i] = bf16r(v / (1.0f + expf(-v)));
}
__global__ void fb_gemv(const float* v, const __nv_bfloat16* w, int k, int n, float* y, int act) {
    const int col = blockIdx.x * blockDim.x + threadIdx.x;
    if (col >= n) return;
    float s = 0.f;
    for (int i = 0; i < k; i++) s = fmaf(v[i], __bfloat162float(w[(size_t)i * n + col]), s);
    s = bf16r(s);
    y[col] = act ? bf16r(s / (1.0f + expf(-s))) : s;
}
__global__ void fb_norm(const float* x, const float* scale, const float* shift, float* h) {
    __shared__ float red[D];
    const int i = threadIdx.x;
    red[i] = x[i];
    __syncthreads();
    float m = 0.f, v = 0.f;
    for (int k = 0; k < D; k++) m += red[k];
    m *= 1.0f / D;
    for (int k = 0; k < D; k++) v = fmaf(red[k] - m, red[k] - m, v);
    const float den = bf16r(sqrtf(bf16r(bf16r(v * (1.0f / D)) + 1e-5f)));
    h[i] = modulate(bf16r(bf16r(x[i] - bf16r(m)) / den), bf16r(1.f + scale[i]), shift[i]);
}
__global__ void fb_attention(const __nv_bfloat16* kc, const __nv_bfloat16* vc) {
    __shared__ float s[WINDOW], red[256];
    const int hq = blockIdx.x, tid = threadIdx.x;
    const size_t base = ((size_t)(hq / 2) * SK + (SK - WINDOW)) * DH;
    float mx = -INFINITY;
    for (int p = tid; p < WINDOW; p += 256) {
        float a = 0.f;
        for (int d = 0; d < DH; d++) a = fmaf(g_fb.q[hq * DH + d], __bfloat162float(kc[base + (size_t)p * DH + d]), a);
        s[p] = bf16r(bf16r(a) * 0.08838834764831845f);
        mx = fmaxf(mx, s[p]);
    }
    red[tid] = mx;
    __syncthreads();
    for (int i = 0; i < 256; i++) mx = fmaxf(mx, red[i]);
    __syncthreads();
    float l = 0.f;
    for (int p = tid; p < WINDOW; p += 256) { s[p] = expf(s[p] - mx); l += s[p]; }
    red[tid] = l;
    __syncthreads();
    l = 0.f;
    for (int i = 0; i < 256; i++) l += red[i];
    if (tid < DH) {
        float a = 0.f;
        for (int p = 0; p < WINDOW; p++) a = fmaf(bf16r(s[p] / l), __bfloat162float(vc[base + (size_t)p * DH + tid]), a);
        g_fb.o[hq * DH + tid] = bf16r(a);
    }
}
__global__ void fb_residual(const float* x, const float* gate, const float* y, float* x2, __nv_bfloat16* out) {
    const int i = threadIdx.x;
    const float v = bf16r(x[i] + bf16r(gate[i] * y[i]));
    if (x2) x2[i] = v;
    if (out) out[i] = __float2bfloat16_rn(v);
}
void launch_fallback(void* const* d_in, void* d_out) {
    typedef const __nv_bfloat16* P;
    Fallback* f = nullptr;
    cudaGetSymbolAddress((void**)&f, g_fb);
    cudaStream_t st = cudaStreamPerThread;
    fb_prepare<<<1, D, 0, st>>>((P)d_in[0], (P)d_in[8]);
    fb_gemv<<<6 * D / 64, 64, 0, st>>>(f->sc, (P)d_in[9], D, 6 * D, f->mod, 0);
    fb_norm<<<1, D, 0, st>>>(f->x, f->mod + D, f->mod, f->h);
    fb_gemv<<<64, 64, 0, st>>>(f->h, (P)d_in[3], D, 4096, f->q, 0);
    fb_attention<<<32, 256, 0, st>>>((P)d_in[1], (P)d_in[2]);
    fb_gemv<<<D / 64, 64, 0, st>>>(f->o, (P)d_in[4], 4096, D, f->y, 0);
    fb_residual<<<1, D, 0, st>>>(f->x, f->mod + 2 * D, f->y, f->x2, nullptr);
    fb_norm<<<1, D, 0, st>>>(f->x2, f->mod + 4 * D, f->mod + 3 * D, f->h);
    fb_gemv<<<FF / 64, 64, 0, st>>>(f->h, (P)d_in[6], D, FF, f->u, 1);
    fb_gemv<<<D / 64, 64, 0, st>>>(f->u, (P)d_in[7], FF, D, f->y, 0);
    fb_residual<<<1, D, 0, st>>>(f->x2, f->mod + 5 * D, f->y, nullptr, (__nv_bfloat16*)d_out);
}

}

extern "C" void kernel_launch(void* const* d_in, const int* in_sizes, int n_in, void* d_out, int out_size) {
    (void)in_sizes; (void)n_in; (void)out_size;
    cudaFuncSetAttribute(adaln_decode_kernel, cudaFuncAttributeMaxDynamicSharedMemorySize, SMEM_BYTES);
    cudaLaunchConfig_t cfg = {};
    cfg.gridDim = dim3(NKV * CS);
    cfg.blockDim = dim3(NTHREADS);
    cfg.dynamicSmemBytes = SMEM_BYTES;
    cfg.stream = cudaStreamPerThread;
    cudaLaunchAttribute at[1];
    at[0].id = cudaLaunchAttributeClusterDimension;
    at[0].val.clusterDim.x = CS;
    at[0].val.clusterDim.y = 1;
    at[0].val.clusterDim.z = 1;
    cfg.attrs = at;
    cfg.numAttrs = 1;

    void* fn = nullptr;
    cudaDriverEntryPointQueryResult qr;
    int clusters = 0;
    const bool ok = cudaOccupancyMaxActiveClusters(&clusters, adaln_decode_kernel, &cfg) == cudaSuccess && clusters >= NKV &&
                    cudaGetDriverEntryPoint("cuTensorMapEncodeTiled", &fn, cudaEnableDefault, &qr) == cudaSuccess && fn;
    if (!ok) {
        (void)cudaGetLastError();
        launch_fallback(d_in, d_out);
        return;
    }
    EncodeTiledFn enc = (EncodeTiledFn)fn;
    Maps maps;
    encode2d(enc, &maps.mod, d_in[9], D, 6 * D, 104, 72, CU_TENSOR_MAP_SWIZZLE_NONE, CU_TENSOR_MAP_L2_PROMOTION_L2_128B);
    encode2d(enc, &maps.gb, d_in[9], D, 6 * D, 24, 192, CU_TENSOR_MAP_SWIZZLE_NONE, CU_TENSOR_MAP_L2_PROMOTION_L2_128B);
    encode3d(enc, &maps.wq, d_in[3], 64, D, 64, 4096 * 2, 128, 64, 32, 4, CU_TENSOR_MAP_SWIZZLE_128B);
    encode3d(enc, &maps.k, d_in[1], 64, (uint64_t)NKV * SK, 2, 256, 128, 64, 64, 2, CU_TENSOR_MAP_SWIZZLE_128B);
    encode3d(enc, &maps.v, d_in[2], 64, (uint64_t)NKV * SK, 2, 256, 128, 64, 64, 2, CU_TENSOR_MAP_SWIZZLE_128B);
    encode2d(enc, &maps.wo, d_in[4], 4096, D, 104, 64, CU_TENSOR_MAP_SWIZZLE_NONE, CU_TENSOR_MAP_L2_PROMOTION_L2_128B);
    encode2d(enc, &maps.w1, d_in[6], D, FF, 56, 144, CU_TENSOR_MAP_SWIZZLE_NONE, CU_TENSOR_MAP_L2_PROMOTION_L2_128B);
    encode2d(enc, &maps.w2, d_in[7], FF, D, 104, 96, CU_TENSOR_MAP_SWIZZLE_NONE, CU_TENSOR_MAP_L2_PROMOTION_L2_128B);
    cudaLaunchKernelEx(&cfg, adaln_decode_kernel, maps, (const __nv_bfloat16*)d_in[0], (const __nv_bfloat16*)d_in[8],
                       (__nv_bfloat16*)d_out);
}
```
